```python
import torch

def _softmax(x, axis=-1):
    return torch.softmax(x, dim=axis)
def _gelu(x):
    return torch.nn.functional.gelu(x, approximate="tanh")
def _silu(x):
    return torch.nn.functional.silu(x)
def _sigmoid(x):
    return torch.sigmoid(x)
def _layernorm(x, axis=-1, eps=1e-5):
    m = x.mean(dim=axis, keepdim=True)
    v = x.var(dim=axis, keepdim=True, unbiased=False)
    return (x - m) / torch.sqrt(v + eps)
def _scatter_add(tgt, idx, src, axis=0):
    return tgt.clone().index_add_(axis, idx, src)
def _segment_sum(src, seg, n):
    out = torch.zeros((n,) + src.shape[1:], dtype=src.dtype)
    return out.index_add_(0, seg, src)
def _pad(x, pw):
    flat = tuple(v for pair in reversed(pw) for v in pair)
    return torch.nn.functional.pad(x, flat)

kernel_name = 'gated_mix__ssm_conv_s4__linear_kernel_hedgehog__prompt'

def setup_inputs():

    _w = (lambda a: (lambda t: t.to(torch.bfloat16) if t.is_floating_point() else t)(torch.as_tensor(a)))
    def _A_setup():
        B, L, D, N = 1, 2048, 1024, 128
        A_re = -(lambda _x: torch.exp(torch.as_tensor(_x)))((lambda *s: torch.randn(*s, dtype=torch.bfloat16) * 6.4)(D, N))
        A_im = torch.pi * (lambda *s: torch.randn(*s, dtype=torch.bfloat16) * 0.1)(D, N)
        B_re = (lambda *s: torch.randn(*s, dtype=torch.bfloat16) * 0.2)(D, N)
        B_im = (lambda *s: torch.randn(*s, dtype=torch.bfloat16) * 0.2)(D, N)
        C_re = (lambda *s: torch.randn(*s, dtype=torch.bfloat16) * 0.2)(D, N)
        C_im = (lambda *s: torch.randn(*s, dtype=torch.bfloat16) * 0.2)(D, N)
        log_dt = (lambda *s: torch.randn(*s, dtype=torch.bfloat16) * 0.1)(D) * 0.5 - 4.0
        Dskip = (lambda *s: torch.randn(*s, dtype=torch.bfloat16) * 0.1)(D)
        return {
            "u": _w((lambda *s: torch.randn(*s, dtype=torch.bfloat16) * 0.05)(B, L, D)),
            "A_re": _w(A_re),
            "A_im": _w(A_im),
            "B_re": _w(B_re),
            "B_im": _w(B_im),
            "C_re": _w(C_re),
            "C_im": _w(C_im),
            "log_dt": _w(log_dt),
            "Dskip": _w(Dskip),
        }
    _A_in = _A_setup()

    def _B_setup():
        B, S, D, H = 1, 2048, 1024, 32
        Dh = D // H
        return {
            "x": _w((lambda *s: torch.randn(*s, dtype=torch.bfloat16) * 0.05)(B, S, D)),
            "wqkv": _w((lambda *s: torch.randn(*s, dtype=torch.bfloat16) * 0.8)(D, 3 * D)),
            "w_phi": _w((lambda *s: torch.randn(*s, dtype=torch.bfloat16) * 0.8)(H, Dh, Dh) * (Dh ** -0.5)),
            "wo": _w((lambda *s: torch.randn(*s, dtype=torch.bfloat16) * 0.05)(D, D)),
        }
    _B_in = _B_setup()

    return {
        "A_u": _A_in["u"],
        "A_A_re": _A_in["A_re"],
        "A_A_im": _A_in["A_im"],
        "A_B_re": _A_in["B_re"],
        "A_B_im": _A_in["B_im"],
        "A_C_re": _A_in["C_re"],
        "A_C_im": _A_in["C_im"],
        "A_log_dt": _A_in["log_dt"],
        "A_Dskip": _A_in["Dskip"],
        "B_x": _B_in["x"],
        "B_wqkv": _B_in["wqkv"],
        "B_w_phi": _B_in["w_phi"],
        "B_wo": _B_in["wo"],
        "gate_w": _w((lambda *s: torch.randn(*s, dtype=torch.bfloat16) * 0.05)(1024) * 16.0),
    }

def reference(A_u, A_A_re, A_A_im, A_B_re, A_B_im, A_C_re, A_C_im, A_log_dt, A_Dskip, B_x, B_wqkv, B_w_phi, B_wo, gate_w):
    def _A_ref(u, A_re, A_im, B_re, B_im, C_re, C_im, log_dt, Dskip):
        Bsz, L, D = u.shape
        dt = torch.exp(log_dt)[:, None]
        A = A_re + 1j * A_im
        Bc = B_re + 1j * B_im
        Cc = C_re + 1j * C_im
        logdA = dt * A
        dB = dt * Bc
        l = (lambda x, dt: x.to(dt))(torch.arange(L), A_re.dtype)
        P = torch.exp(logdA[:, :, None] * l[None, None, :])
        K = torch.einsum("dn,dnl,dn->dl", Cc, P, dB).real
        L2 = 2 * L
        Kp = _pad(K, ((0, 0), (0, L)))
        up = (lambda x, *d: x.permute(*d))(u, 0, 2, 1)
        up = _pad(up, ((0, 0), (0, 0), (0, L)))
        Kf = (lambda x, axes=(-2,-1): torch.fft.rfft2(x.float(), dim=axes))(Kp[:, None, :], axes=(-2, -1))
        Uf = (lambda x, axes=(-2,-1): torch.fft.rfft2(x.float(), dim=axes))(up[:, :, None, :], axes=(-2, -1))
        Yf = Uf * Kf[None, :, :, :]
        y = (lambda x, s, axes=(-2,-1): torch.fft.irfft2(x, s=s, dim=axes).to(torch.bfloat16))(Yf, (1, L2), axes=(-2, -1))[:, :, 0, :L]
        y = (lambda x, *d: x.permute(*d))(y, 0, 2, 1) + u * Dskip[None, None, :]
        return y

    def _B_ref(x, wqkv, w_phi, wo):
        B, S, D = x.shape
        H = 32; Dh = D // H
        qkv = (lambda x, *d: x.permute(*d))((x @ wqkv).reshape(B, S, 3, H, Dh), 2, 0, 3, 1, 4)
        q, k, v = qkv[0], qkv[1], qkv[2]
        pq = torch.einsum("bhsd,hdf->bhsf", q, w_phi)
        pk = torch.einsum("bhsd,hdf->bhsf", k, w_phi)
        phi_q = torch.concatenate([_softmax(pq, axis=-1), _softmax(-pq, axis=-1)], axis=-1)
        phi_k = torch.concatenate([_softmax(pk, axis=-1), _softmax(-pk, axis=-1)], axis=-1)
        kv = torch.einsum("bhsf,bhsd->bhfd", phi_k, v)
        z  = torch.einsum("bhsf->bhf", phi_k)
        num = torch.einsum("bhqf,bhfd->bhqd", phi_q, kv)
        den = torch.einsum("bhqf,bhf->bhq", phi_q, z)[..., None] + 1e-6
        o = num / den
        return (lambda x, *d: x.permute(*d))(o, 0, 2, 1, 3).reshape(B, S, D) @ wo

    x = A_u
    g = _sigmoid((x * gate_w).sum(-1, keepdims=True))
    a = _A_ref(x, A_A_re, A_A_im, A_B_re, A_B_im, A_C_re, A_C_im, A_log_dt, A_Dskip)
    b = _B_ref(x, B_wqkv, B_w_phi, B_wo)
    return g * a + (1 - g) * b
```

```cpp
#include <cuda_runtime.h>
#include <cuda_bf16.h>
#include <cuda.h>
#include <stdint.h>

typedef __nv_bfloat16 bf16;

__device__ __forceinline__ uint32_t smem_u32(const void* p) { return (uint32_t)__cvta_generic_to_shared(p); }
__device__ __forceinline__ void mbar_init(uint32_t bar, uint32_t cnt) { asm volatile("mbarrier.init.shared::cta.b64 [%0], %1;" ::"r"(bar), "r"(cnt) : "memory"); }
__device__ __forceinline__ void mbar_expect_tx(uint32_t bar, uint32_t bytes) { asm volatile("mbarrier.arrive.expect_tx.shared::cta.b64 _, [%0], %1;" ::"r"(bar), "r"(bytes) : "memory"); }
__device__ __forceinline__ void mbar_arrive(uint32_t bar) { asm volatile("mbarrier.arrive.shared::cta.b64 _, [%0];" ::"r"(bar) : "memory"); }
__device__ __forceinline__ bool mbar_test(uint32_t bar, uint32_t parity) {
  uint32_t ok;
  asm volatile("{.reg .pred p; mbarrier.test_wait.parity.shared::cta.b64 p, [%1], %2; selp.u32 %0, 1, 0, p;}" : "=r"(ok) : "r"(bar), "r"(parity) : "memory");
  return ok != 0;
}
__device__ __forceinline__ bool mbar_try(uint32_t bar, uint32_t parity) {
  uint32_t ok;
  asm volatile("{.reg .pred p; mbarrier.try_wait.parity.shared::cta.b64 p, [%1], %2; selp.u32 %0, 1, 0, p;}" : "=r"(ok) : "r"(bar), "r"(parity) : "memory");
  return ok != 0;
}
__device__ __forceinline__ void mbar_wait(uint32_t bar, uint32_t parity) {
  asm volatile("{.reg .pred p; .reg .u32 cnt; mov.u32 cnt, 0;\nLW: mbarrier.try_wait.parity.shared::cta.b64 p, [%0], %1, 100000; @p bra LD; add.u32 cnt, cnt, 1; setp.lt.u32 p, cnt, 20000; @p bra LW; trap;\nLD: }" ::"r"(bar), "r"(parity) : "memory");
}
__device__ __forceinline__ bool elect_one() {
  uint32_t p;
  asm volatile("{.reg .pred P; elect.sync _|P, 0xffffffff; selp.u32 %0, 1, 0, P;}" : "=r"(p));
  return p != 0;
}
__device__ __forceinline__ void bar_sync(int id, int n) { asm volatile("bar.sync %0, %1;" ::"r"(id), "r"(n) : "memory"); }
__device__ __forceinline__ void bar_arrive(int id, int n) { asm volatile("bar.arrive %0, %1;" ::"r"(id), "r"(n) : "memory"); }
__device__ __forceinline__ void fence_async_smem() { asm volatile("fence.proxy.async.shared::cta;" ::: "memory"); }
__device__ __forceinline__ void wg_fence() { asm volatile("wgmma.fence.sync.aligned;" ::: "memory"); }
__device__ __forceinline__ void wg_commit() { asm volatile("wgmma.commit_group.sync.aligned;" ::: "memory"); }
template <int N> __device__ __forceinline__ void wg_wait() { asm volatile("wgmma.wait_group.sync.aligned %0;" ::"n"(N) : "memory"); }

__device__ __forceinline__ void tma_2d(uint32_t dst, const CUtensorMap* m, int c0, int c1, uint32_t bar) {
  asm volatile("cp.async.bulk.tensor.2d.shared::cluster.global.mbarrier::complete_tx::bytes [%0], [%1, {%3, %4}], [%2];" ::"r"(dst), "l"(m), "r"(bar), "r"(c0), "r"(c1) : "memory");
}
__device__ __forceinline__ void tma_3d(uint32_t dst, const CUtensorMap* m, int c0, int c1, int c2, uint32_t bar) {
  asm volatile("cp.async.bulk.tensor.3d.shared::cluster.global.mbarrier::complete_tx::bytes [%0], [%1, {%3, %4, %5}], [%2];" ::"r"(dst), "l"(m), "r"(bar), "r"(c0), "r"(c1), "r"(c2) : "memory");
}
__device__ __forceinline__ void tma_5d(uint32_t dst, const CUtensorMap* m, int c0, int c1, int c2, int c3, int c4, uint32_t bar) {
  asm volatile("cp.async.bulk.tensor.5d.shared::cluster.global.mbarrier::complete_tx::bytes [%0], [%1, {%3, %4, %5, %6, %7}], [%2];" ::"r"(dst), "l"(m), "r"(bar), "r"(c0), "r"(c1), "r"(c2), "r"(c3), "r"(c4) : "memory");
}
__device__ __forceinline__ void prefetch_map(const CUtensorMap* m) { asm volatile("prefetch.tensormap [%0];" ::"l"(m) : "memory"); }
__device__ __forceinline__ void tma_st_2d(const CUtensorMap* m, int c0, int c1, uint32_t src) {
  asm volatile("cp.async.bulk.tensor.2d.global.shared::cta.bulk_group [%0, {%2, %3}], [%1];" ::"l"(m), "r"(src), "r"(c0), "r"(c1) : "memory");
}
__device__ __forceinline__ void bulk_g2s(uint32_t dst, const void* src, uint32_t bytes, uint32_t bar) {
  asm volatile("cp.async.bulk.shared::cluster.global.mbarrier::complete_tx::bytes [%0], [%1], %2, [%3];" ::"r"(dst), "l"(src), "r"(bytes), "r"(bar) : "memory");
}
__device__ __forceinline__ void bulk_commit() { asm volatile("cp.async.bulk.commit_group;" ::: "memory"); }
__device__ __forceinline__ void bulk_wait0() { asm volatile("cp.async.bulk.wait_group 0;" ::: "memory"); }
__device__ __forceinline__ void bulk_wait0_read() { asm volatile("cp.async.bulk.wait_group.read 0;" ::: "memory"); }
__device__ __forceinline__ void cp_async16(uint32_t dst, const void* src) { asm volatile("cp.async.cg.shared.global [%0], [%1], 16;" ::"r"(dst), "l"(src) : "memory"); }
__device__ __forceinline__ void cp_async_commit() { asm volatile("cp.async.commit_group;" ::: "memory"); }
template <int N> __device__ __forceinline__ void cp_async_wait() { asm volatile("cp.async.wait_group %0;" ::"n"(N) : "memory"); }

__device__ __forceinline__ uint64_t mkdesc(uint32_t addr, uint32_t lbo, uint32_t sbo, uint32_t swz) {
  return (uint64_t)((addr & 0x3FFFF) >> 4) | ((uint64_t)(lbo >> 4) << 16) | ((uint64_t)(sbo >> 4) << 32) | ((uint64_t)swz << 62);
}
__device__ __forceinline__ void ldsm4(uint32_t a, uint32_t& r0, uint32_t& r1, uint32_t& r2, uint32_t& r3) {
  asm volatile("ldmatrix.sync.aligned.m8n8.x4.shared.b16 {%0,%1,%2,%3}, [%4];" : "=r"(r0), "=r"(r1), "=r"(r2), "=r"(r3) : "r"(a) : "memory");
}
__device__ __forceinline__ void ldsm4t(uint32_t a, uint32_t& r0, uint32_t& r1, uint32_t& r2, uint32_t& r3) {
  asm volatile("ldmatrix.sync.aligned.m8n8.x4.trans.shared.b16 {%0,%1,%2,%3}, [%4];" : "=r"(r0), "=r"(r1), "=r"(r2), "=r"(r3) : "r"(a) : "memory");
}
__device__ __forceinline__ void stsm4(uint32_t a, uint32_t r0, uint32_t r1, uint32_t r2, uint32_t r3) {
  asm volatile("stmatrix.sync.aligned.m8n8.x4.shared.b16 [%0], {%1,%2,%3,%4};" ::"r"(a), "r"(r0), "r"(r1), "r"(r2), "r"(r3) : "memory");
}
__device__ __forceinline__ void stsm4t(uint32_t a, uint32_t r0, uint32_t r1, uint32_t r2, uint32_t r3) {
  asm volatile("stmatrix.sync.aligned.m8n8.x4.trans.shared.b16 [%0], {%1,%2,%3,%4};" ::"r"(a), "r"(r0), "r"(r1), "r"(r2), "r"(r3) : "memory");
}
__device__ __forceinline__ uint32_t lds32(uint32_t a) { uint32_t v; asm volatile("ld.shared.u32 %0, [%1];" : "=r"(v) : "r"(a) : "memory"); return v; }
__device__ __forceinline__ uint32_t lds16(uint32_t a) { uint32_t v; asm volatile("ld.shared.u16 %0, [%1];" : "=r"(v) : "r"(a) : "memory"); return v; }
__device__ __forceinline__ uint2 lds64(uint32_t a) { uint2 v; asm volatile("ld.shared.v2.u32 {%0,%1}, [%2];" : "=r"(v.x), "=r"(v.y) : "r"(a) : "memory"); return v; }
__device__ __forceinline__ uint4 lds128(uint32_t a) { uint4 v; asm volatile("ld.shared.v4.u32 {%0,%1,%2,%3}, [%4];" : "=r"(v.x), "=r"(v.y), "=r"(v.z), "=r"(v.w) : "r"(a) : "memory"); return v; }
__device__ __forceinline__ void sts16(uint32_t a, uint32_t v) { asm volatile("st.shared.u16 [%0], %1;" ::"r"(a), "h"((unsigned short)v) : "memory"); }
__device__ __forceinline__ void sts32(uint32_t a, uint32_t v) { asm volatile("st.shared.u32 [%0], %1;" ::"r"(a), "r"(v) : "memory"); }
__device__ __forceinline__ void sts64(uint32_t a, uint32_t x, uint32_t y) { asm volatile("st.shared.v2.u32 [%0], {%1,%2};" ::"r"(a), "r"(x), "r"(y) : "memory"); }
__device__ __forceinline__ void sts128(uint32_t a, uint32_t x, uint32_t y, uint32_t z, uint32_t w) { asm volatile("st.shared.v4.u32 [%0], {%1,%2,%3,%4};" ::"r"(a), "r"(x), "r"(y), "r"(z), "r"(w) : "memory"); }
__device__ __forceinline__ uint32_t pk(float lo, float hi) { uint32_t r; asm("cvt.rn.bf16x2.f32 %0, %1, %2;" : "=r"(r) : "f"(hi), "f"(lo)); return r; }
__device__ __forceinline__ float bflo(uint32_t v) { return __uint_as_float(v << 16); }
__device__ __forceinline__ float bfhi(uint32_t v) { return __uint_as_float(v & 0xffff0000u); }
__device__ __forceinline__ float ex2(float x) { float y; asm("ex2.approx.ftz.f32 %0, %1;" : "=f"(y) : "f"(x)); return y; }
__device__ __forceinline__ float rcp(float x) { float y; asm("rcp.approx.ftz.f32 %0, %1;" : "=f"(y) : "f"(x)); return y; }
__device__ __forceinline__ uint32_t hadd2(uint32_t a, uint32_t b) { uint32_t r; asm("add.rn.bf16x2 %0, %1, %2;" : "=r"(r) : "r"(a), "r"(b)); return r; }
__device__ __forceinline__ uint32_t hmul2(uint32_t a, uint32_t b) { uint32_t r; asm("mul.rn.bf16x2 %0, %1, %2;" : "=r"(r) : "r"(a), "r"(b)); return r; }
__device__ __forceinline__ uint32_t hmax2(uint32_t a, uint32_t b) { uint32_t r; asm("max.bf16x2 %0, %1, %2;" : "=r"(r) : "r"(a), "r"(b)); return r; }
__device__ __forceinline__ uint32_t hmin2(uint32_t a, uint32_t b) { uint32_t r; asm("min.bf16x2 %0, %1, %2;" : "=r"(r) : "r"(a), "r"(b)); return r; }
__device__ __forceinline__ uint32_t ld_acq(const uint32_t* p) { uint32_t v; asm volatile("ld.acquire.gpu.global.u32 %0, [%1];" : "=r"(v) : "l"(p) : "memory"); return v; }
__device__ __forceinline__ uint32_t ld_rlx(const uint32_t* p) { uint32_t v; asm volatile("ld.relaxed.gpu.global.u32 %0, [%1];" : "=r"(v) : "l"(p) : "memory"); return v; }
__device__ __forceinline__ void st_rlx(uint32_t* p, uint32_t v) { asm volatile("st.relaxed.gpu.global.u32 [%0], %1;" ::"l"(p), "r"(v) : "memory"); }
__device__ __forceinline__ void red_rlx(uint32_t* p, uint32_t v) { asm volatile("red.relaxed.gpu.global.add.u32 [%0], %1;" ::"l"(p), "r"(v) : "memory"); }
__device__ __forceinline__ void red_rel(uint32_t* p, uint32_t v) { asm volatile("red.release.gpu.global.add.u32 [%0], %1;" ::"l"(p), "r"(v) : "memory"); }
__device__ __forceinline__ void wg_p1_n192(float (&d)[96], uint64_t da, uint64_t db, int sc) {
  asm volatile("{.reg .pred p; setp.ne.b32 p, %98, 0; wgmma.mma_async.sync.aligned.m64n192k16.f32.bf16.bf16 {%0, %1, %2, %3, %4, %5, %6, %7, %8, %9, %10, %11, %12, %13, %14, %15, %16, %17, %18, %19, %20, %21, %22, %23, %24, %25, %26, %27, %28, %29, %30, %31, %32, %33, %34, %35, %36, %37, %38, %39, %40, %41, %42, %43, %44, %45, %46, %47, %48, %49, %50, %51, %52, %53, %54, %55, %56, %57, %58, %59, %60, %61, %62, %63, %64, %65, %66, %67, %68, %69, %70, %71, %72, %73, %74, %75, %76, %77, %78, %79, %80, %81, %82, %83, %84, %85, %86, %87, %88, %89, %90, %91, %92, %93, %94, %95}, %96, %97, p, 1, 1, 0, 1;}"
    : "+f"(d[0]), "+f"(d[1]), "+f"(d[2]), "+f"(d[3]), "+f"(d[4]), "+f"(d[5]), "+f"(d[6]), "+f"(d[7]), "+f"(d[8]), "+f"(d[9]), "+f"(d[10]), "+f"(d[11]), "+f"(d[12]), "+f"(d[13]), "+f"(d[14]), "+f"(d[15]), "+f"(d[16]), "+f"(d[17]), "+f"(d[18]), "+f"(d[19]), "+f"(d[20]), "+f"(d[21]), "+f"(d[22]), "+f"(d[23]), "+f"(d[24]), "+f"(d[25]), "+f"(d[26]), "+f"(d[27]), "+f"(d[28]), "+f"(d[29]), "+f"(d[30]), "+f"(d[31]), "+f"(d[32]), "+f"(d[33]), "+f"(d[34]), "+f"(d[35]), "+f"(d[36]), "+f"(d[37]), "+f"(d[38]), "+f"(d[39]), "+f"(d[40]), "+f"(d[41]), "+f"(d[42]), "+f"(d[43]), "+f"(d[44]), "+f"(d[45]), "+f"(d[46]), "+f"(d[47]), "+f"(d[48]), "+f"(d[49]), "+f"(d[50]), "+f"(d[51]), "+f"(d[52]), "+f"(d[53]), "+f"(d[54]), "+f"(d[55]), "+f"(d[56]), "+f"(d[57]), "+f"(d[58]), "+f"(d[59]), "+f"(d[60]), "+f"(d[61]), "+f"(d[62]), "+f"(d[63]), "+f"(d[64]), "+f"(d[65]), "+f"(d[66]), "+f"(d[67]), "+f"(d[68]), "+f"(d[69]), "+f"(d[70]), "+f"(d[71]), "+f"(d[72]), "+f"(d[73]), "+f"(d[74]), "+f"(d[75]), "+f"(d[76]), "+f"(d[77]), "+f"(d[78]), "+f"(d[79]), "+f"(d[80]), "+f"(d[81]), "+f"(d[82]), "+f"(d[83]), "+f"(d[84]), "+f"(d[85]), "+f"(d[86]), "+f"(d[87]), "+f"(d[88]), "+f"(d[89]), "+f"(d[90]), "+f"(d[91]), "+f"(d[92]), "+f"(d[93]), "+f"(d[94]), "+f"(d[95])
    : "l"(da), "l"(db), "r"(sc));
}
__device__ __forceinline__ void wg_kg_n16(float (&d)[8], uint32_t a0, uint32_t a1, uint32_t a2, uint32_t a3, uint64_t db) {
  asm volatile("wgmma.mma_async.sync.aligned.m64n16k16.f32.bf16.bf16 {%0, %1, %2, %3, %4, %5, %6, %7}, {%8, %9, %10, %11}, %12, 1, 1, 1, 1;"
    : "+f"(d[0]), "+f"(d[1]), "+f"(d[2]), "+f"(d[3]), "+f"(d[4]), "+f"(d[5]), "+f"(d[6]), "+f"(d[7])
    : "r"(a0), "r"(a1), "r"(a2), "r"(a3), "l"(db));
}
__device__ __forceinline__ void wg_kg_n16_d(float (&d)[8], uint32_t a0, uint32_t a1, uint32_t a2, uint32_t a3, uint64_t db, int sc) {
  asm volatile("{.reg .pred p; setp.ne.b32 p, %13, 0; wgmma.mma_async.sync.aligned.m64n16k16.f32.bf16.bf16 {%0, %1, %2, %3, %4, %5, %6, %7}, {%8, %9, %10, %11}, %12, p, 1, 1, 1;}"
    : "+f"(d[0]), "+f"(d[1]), "+f"(d[2]), "+f"(d[3]), "+f"(d[4]), "+f"(d[5]), "+f"(d[6]), "+f"(d[7])
    : "r"(a0), "r"(a1), "r"(a2), "r"(a3), "l"(db), "r"(sc));
}
__device__ __forceinline__ void wg_cv_z(float (&d)[16], uint32_t a0, uint32_t a1, uint32_t a2, uint32_t a3, uint64_t db) {
  asm volatile("wgmma.mma_async.sync.aligned.m64n32k16.f32.bf16.bf16 {%0, %1, %2, %3, %4, %5, %6, %7, %8, %9, %10, %11, %12, %13, %14, %15}, {%16, %17, %18, %19}, %20, 0, 1, 1, 0;"
    : "+f"(d[0]), "+f"(d[1]), "+f"(d[2]), "+f"(d[3]), "+f"(d[4]), "+f"(d[5]), "+f"(d[6]), "+f"(d[7]), "+f"(d[8]), "+f"(d[9]), "+f"(d[10]), "+f"(d[11]), "+f"(d[12]), "+f"(d[13]), "+f"(d[14]), "+f"(d[15])
    : "r"(a0), "r"(a1), "r"(a2), "r"(a3), "l"(db));
}
__device__ __forceinline__ void wg_cv(float (&d)[16], uint32_t a0, uint32_t a1, uint32_t a2, uint32_t a3, uint64_t db) {
  asm volatile("wgmma.mma_async.sync.aligned.m64n32k16.f32.bf16.bf16 {%0, %1, %2, %3, %4, %5, %6, %7, %8, %9, %10, %11, %12, %13, %14, %15}, {%16, %17, %18, %19}, %20, 1, 1, 1, 0;"
    : "+f"(d[0]), "+f"(d[1]), "+f"(d[2]), "+f"(d[3]), "+f"(d[4]), "+f"(d[5]), "+f"(d[6]), "+f"(d[7]), "+f"(d[8]), "+f"(d[9]), "+f"(d[10]), "+f"(d[11]), "+f"(d[12]), "+f"(d[13]), "+f"(d[14]), "+f"(d[15])
    : "r"(a0), "r"(a1), "r"(a2), "r"(a3), "l"(db));
}
__device__ __forceinline__ void wg_phi_n32_z(float (&d)[16], uint32_t a0, uint32_t a1, uint32_t a2, uint32_t a3, uint64_t db) {
  asm volatile("wgmma.mma_async.sync.aligned.m64n32k16.f32.bf16.bf16 {%0, %1, %2, %3, %4, %5, %6, %7, %8, %9, %10, %11, %12, %13, %14, %15}, {%16, %17, %18, %19}, %20, 0, 1, 1, 1;"
    : "+f"(d[0]), "+f"(d[1]), "+f"(d[2]), "+f"(d[3]), "+f"(d[4]), "+f"(d[5]), "+f"(d[6]), "+f"(d[7]), "+f"(d[8]), "+f"(d[9]), "+f"(d[10]), "+f"(d[11]), "+f"(d[12]), "+f"(d[13]), "+f"(d[14]), "+f"(d[15])
    : "r"(a0), "r"(a1), "r"(a2), "r"(a3), "l"(db));
}
__device__ __forceinline__ void wg_phi_n32(float (&d)[16], uint32_t a0, uint32_t a1, uint32_t a2, uint32_t a3, uint64_t db) {
  asm volatile("wgmma.mma_async.sync.aligned.m64n32k16.f32.bf16.bf16 {%0, %1, %2, %3, %4, %5, %6, %7, %8, %9, %10, %11, %12, %13, %14, %15}, {%16, %17, %18, %19}, %20, 1, 1, 1, 1;"
    : "+f"(d[0]), "+f"(d[1]), "+f"(d[2]), "+f"(d[3]), "+f"(d[4]), "+f"(d[5]), "+f"(d[6]), "+f"(d[7]), "+f"(d[8]), "+f"(d[9]), "+f"(d[10]), "+f"(d[11]), "+f"(d[12]), "+f"(d[13]), "+f"(d[14]), "+f"(d[15])
    : "r"(a0), "r"(a1), "r"(a2), "r"(a3), "l"(db));
}
__device__ __forceinline__ void wg_kv_n40(float (&d)[20], uint64_t da, uint64_t db, int sc) {
  asm volatile("{.reg .pred p; setp.ne.b32 p, %22, 0; wgmma.mma_async.sync.aligned.m64n40k16.f32.bf16.bf16 {%0, %1, %2, %3, %4, %5, %6, %7, %8, %9, %10, %11, %12, %13, %14, %15, %16, %17, %18, %19}, %20, %21, p, 1, 1, 1, 1;}"
    : "+f"(d[0]), "+f"(d[1]), "+f"(d[2]), "+f"(d[3]), "+f"(d[4]), "+f"(d[5]), "+f"(d[6]), "+f"(d[7]), "+f"(d[8]), "+f"(d[9]), "+f"(d[10]), "+f"(d[11]), "+f"(d[12]), "+f"(d[13]), "+f"(d[14]), "+f"(d[15]), "+f"(d[16]), "+f"(d[17]), "+f"(d[18]), "+f"(d[19])
    : "l"(da), "l"(db), "r"(sc));
}
__device__ __forceinline__ void wg_o_n40_z(float (&d)[20], uint32_t a0, uint32_t a1, uint32_t a2, uint32_t a3, uint64_t db) {
  asm volatile("wgmma.mma_async.sync.aligned.m64n40k16.f32.bf16.bf16 {%0, %1, %2, %3, %4, %5, %6, %7, %8, %9, %10, %11, %12, %13, %14, %15, %16, %17, %18, %19}, {%20, %21, %22, %23}, %24, 0, 1, 1, 1;"
    : "+f"(d[0]), "+f"(d[1]), "+f"(d[2]), "+f"(d[3]), "+f"(d[4]), "+f"(d[5]), "+f"(d[6]), "+f"(d[7]), "+f"(d[8]), "+f"(d[9]), "+f"(d[10]), "+f"(d[11]), "+f"(d[12]), "+f"(d[13]), "+f"(d[14]), "+f"(d[15]), "+f"(d[16]), "+f"(d[17]), "+f"(d[18]), "+f"(d[19])
    : "r"(a0), "r"(a1), "r"(a2), "r"(a3), "l"(db));
}
__device__ __forceinline__ void wg_o_n40(float (&d)[20], uint32_t a0, uint32_t a1, uint32_t a2, uint32_t a3, uint64_t db) {
  asm volatile("wgmma.mma_async.sync.aligned.m64n40k16.f32.bf16.bf16 {%0, %1, %2, %3, %4, %5, %6, %7, %8, %9, %10, %11, %12, %13, %14, %15, %16, %17, %18, %19}, {%20, %21, %22, %23}, %24, 1, 1, 1, 1;"
    : "+f"(d[0]), "+f"(d[1]), "+f"(d[2]), "+f"(d[3]), "+f"(d[4]), "+f"(d[5]), "+f"(d[6]), "+f"(d[7]), "+f"(d[8]), "+f"(d[9]), "+f"(d[10]), "+f"(d[11]), "+f"(d[12]), "+f"(d[13]), "+f"(d[14]), "+f"(d[15]), "+f"(d[16]), "+f"(d[17]), "+f"(d[18]), "+f"(d[19])
    : "r"(a0), "r"(a1), "r"(a2), "r"(a3), "l"(db));
}
__device__ __forceinline__ void wg_p2_n128(float (&d)[64], uint64_t da, uint64_t db, int sc) {
  asm volatile("{.reg .pred p; setp.ne.b32 p, %66, 0; wgmma.mma_async.sync.aligned.m64n128k16.f32.bf16.bf16 {%0, %1, %2, %3, %4, %5, %6, %7, %8, %9, %10, %11, %12, %13, %14, %15, %16, %17, %18, %19, %20, %21, %22, %23, %24, %25, %26, %27, %28, %29, %30, %31, %32, %33, %34, %35, %36, %37, %38, %39, %40, %41, %42, %43, %44, %45, %46, %47, %48, %49, %50, %51, %52, %53, %54, %55, %56, %57, %58, %59, %60, %61, %62, %63}, %64, %65, p, 1, 1, 0, 1;}"
    : "+f"(d[0]), "+f"(d[1]), "+f"(d[2]), "+f"(d[3]), "+f"(d[4]), "+f"(d[5]), "+f"(d[6]), "+f"(d[7]), "+f"(d[8]), "+f"(d[9]), "+f"(d[10]), "+f"(d[11]), "+f"(d[12]), "+f"(d[13]), "+f"(d[14]), "+f"(d[15]), "+f"(d[16]), "+f"(d[17]), "+f"(d[18]), "+f"(d[19]), "+f"(d[20]), "+f"(d[21]), "+f"(d[22]), "+f"(d[23]), "+f"(d[24]), "+f"(d[25]), "+f"(d[26]), "+f"(d[27]), "+f"(d[28]), "+f"(d[29]), "+f"(d[30]), "+f"(d[31]), "+f"(d[32]), "+f"(d[33]), "+f"(d[34]), "+f"(d[35]), "+f"(d[36]), "+f"(d[37]), "+f"(d[38]), "+f"(d[39]), "+f"(d[40]), "+f"(d[41]), "+f"(d[42]), "+f"(d[43]), "+f"(d[44]), "+f"(d[45]), "+f"(d[46]), "+f"(d[47]), "+f"(d[48]), "+f"(d[49]), "+f"(d[50]), "+f"(d[51]), "+f"(d[52]), "+f"(d[53]), "+f"(d[54]), "+f"(d[55]), "+f"(d[56]), "+f"(d[57]), "+f"(d[58]), "+f"(d[59]), "+f"(d[60]), "+f"(d[61]), "+f"(d[62]), "+f"(d[63])
    : "l"(da), "l"(db), "r"(sc));
}
__device__ __align__(16) const uint32_t g_lut[768] = {
  0x00220022, 0x00220022, 0x00220022, 0x00220022, 0x00220022, 0x00220022, 0x00220022, 0x00000022, 0x00600030, 0x00c00090, 0x012000f0, 0x00020150,
  0x00620032, 0x00c20092, 0x012200f2, 0x00040152, 0x00640034, 0x00c40094, 0x012400f4, 0x00060154, 0x00660036, 0x00c60096, 0x012600f6, 0x00080156,
  0x00680038, 0x00c80098, 0x012800f8, 0x000a0158, 0x006a003a, 0x00ca009a, 0x012a00fa, 0x000c015a, 0x006c003c, 0x00cc009c, 0x012c00fc, 0x000e015c,
  0x006e003e, 0x00ce009e, 0x012e00fe, 0x0010015e, 0x00700040, 0x00d000a0, 0x01300100, 0x00120160, 0x00720042, 0x00d200a2, 0x01320102, 0x00140162,
  0x00740044, 0x00d400a4, 0x01340104, 0x00160164, 0x00760046, 0x00d600a6, 0x01360106, 0x00180166, 0x00780048, 0x00d800a8, 0x01380108, 0x001a0168,
  0x007a004a, 0x00da00aa, 0x013a010a, 0x001c016a, 0x007c004c, 0x00dc00ac, 0x013c010c, 0x001e016c, 0x007e004e, 0x00de00ae, 0x013e010e, 0x0180016e,
  0x01e001b0, 0x02400210, 0x02a00270, 0x018202d0, 0x01e201b2, 0x02420212, 0x02a20272, 0x018402d2, 0x01e401b4, 0x02440214, 0x02a40274, 0x018602d4,
  0x01e601b6, 0x02460216, 0x02a60276, 0x018802d6, 0x01e801b8, 0x02480218, 0x02a80278, 0x018a02d8, 0x01ea01ba, 0x024a021a, 0x02aa027a, 0x018c02da,
  0x01ec01bc, 0x024c021c, 0x02ac027c, 0x018e02dc, 0x01ee01be, 0x024e021e, 0x02ae027e, 0x019002de, 0x01f001c0, 0x02500220, 0x02b00280, 0x019202e0,
  0x01f201c2, 0x02520222, 0x02b20282, 0x019402e2, 0x01f401c4, 0x02540224, 0x02b40284, 0x019602e4, 0x01f601c6, 0x02560226, 0x02b60286, 0x019802e6,
  0x01f801c8, 0x02580228, 0x02b80288, 0x019a02e8, 0x01fa01ca, 0x025a022a, 0x02ba028a, 0x019c02ea, 0x01fc01cc, 0x025c022c, 0x02bc028c, 0x019e02ec,
  0x01fe01ce, 0x025e022e, 0x02be028e, 0x030002ee, 0x03300300, 0x03600360, 0x03900360, 0x03020302, 0x03320302, 0x03620362, 0x03920362, 0x03040304,
  0x03340304, 0x03640364, 0x03940364, 0x03060306, 0x03360306, 0x03660366, 0x03960366, 0x03080308, 0x03380308, 0x03680368, 0x03980368, 0x030a030a,
  0x033a030a, 0x036a036a, 0x039a036a, 0x030c030c, 0x033c030c, 0x036c036c, 0x039c036c, 0x030e030e, 0x033e030e, 0x036e036e, 0x039e036e, 0x03100310,
  0x03400310, 0x03700370, 0x03a00370, 0x03120312, 0x03420312, 0x03720372, 0x03a20372, 0x03140314, 0x03440314, 0x03740374, 0x03a40374, 0x03160316,
  0x03460316, 0x03760376, 0x03a60376, 0x03180318, 0x03480318, 0x03780378, 0x03a80378, 0x031a031a, 0x034a031a, 0x037a037a, 0x03aa037a, 0x031c031c,
  0x034c031c, 0x037c037c, 0x03ac037c, 0x031e031e, 0x034e031e, 0x037e037e, 0x03ae037e, 0x03c003c0, 0x03f003c0, 0x04200420, 0x04500420, 0x03c203c2,
  0x03f203c2, 0x04220422, 0x04520422, 0x03c403c4, 0x03f403c4, 0x04240424, 0x04540424, 0x03c603c6, 0x03f603c6, 0x04260426, 0x04560426, 0x03c803c8,
  0x03f803c8, 0x04280428, 0x04580428, 0x03ca03ca, 0x03fa03ca, 0x042a042a, 0x045a042a, 0x03cc03cc, 0x03fc03cc, 0x042c042c, 0x045c042c, 0x03ce03ce,
  0x03fe03ce, 0x042e042e, 0x045e042e, 0x03d003d0, 0x040003d0, 0x04300430, 0x04600430, 0x03d203d2, 0x040203d2, 0x04320432, 0x04620432, 0x03d403d4,
  0x040403d4, 0x04340434, 0x04640434, 0x03d603d6, 0x040603d6, 0x04360436, 0x04660436, 0x03d803d8, 0x040803d8, 0x04380438, 0x04680438, 0x03da03da,
  0x040a03da, 0x043a043a, 0x046a043a, 0x03dc03dc, 0x040c03dc, 0x043c043c, 0x046c043c, 0x03de03de, 0x040e03de, 0x043e043e, 0x046e043e, 0x04800480,
  0x04800480, 0x04b004b0, 0x048204b0, 0x04820482, 0x04820482, 0x04b204b2, 0x048404b2, 0x04840484, 0x04840484, 0x04b404b4, 0x048604b4, 0x04860486,
  0x04860486, 0x04b604b6, 0x048804b6, 0x04880488, 0x04880488, 0x04b804b8, 0x048a04b8, 0x048a048a, 0x048a048a, 0x04ba04ba, 0x002204ba, 0x00220022,
  0x00220022, 0x00220022, 0x00220022, 0x00220022, 0x00220022, 0x00220022, 0x00220022, 0x00220022, 0x00220022, 0x00220022, 0x00220022, 0x00220022,
  0x00220022, 0x00220022, 0x00220022, 0x00220022, 0x00220022, 0x06000600, 0x06020602, 0x06020602, 0x06020602, 0x06040602, 0x06040604, 0x06040604,
  0x06040604, 0x06040604, 0x06060606, 0x06060606, 0x06060606, 0x06080606, 0x06080608, 0x06080608, 0x06080608, 0x06080608, 0x060a060a, 0x060a060a,
  0x060a060a, 0x0022060a, 0x00220022, 0x00220022, 0x00220022, 0x00220022, 0x00220022, 0x00220022, 0x00220022, 0x00220022, 0x00220022, 0x00220022,
  0x00220022, 0x00220022, 0x00220022, 0x060c0610, 0x06140618, 0x061c0630, 0x06340638, 0x063c0640, 0x06440648, 0x064c0660, 0x06640668, 0x066c0670,
  0x06740678, 0x067c0690, 0x06940698, 0x069c06a0, 0x06a406a8, 0x06ac06c0, 0x06c406c8, 0x06cc06d0, 0x06d406d8, 0x06dc06f0, 0x06f406f8, 0x06fc0700,
  0x07040708, 0x070c0720, 0x07240728, 0x072c0730, 0x07340738, 0x073c0750, 0x07540758, 0x075c0760, 0x07640768, 0x076c0020, 0x00220022, 0x00220022,
  0x00220022, 0x00220022, 0x00220022, 0x0022060e, 0x06120616, 0x061a061e, 0x06320636, 0x063a063e, 0x06420646, 0x064a064e, 0x06620666, 0x066a066e,
  0x06720676, 0x067a067e, 0x06920696, 0x069a069e, 0x06a206a6, 0x06aa06ae, 0x06c206c6, 0x06ca06ce, 0x06d206d6, 0x06da06de, 0x06f206f6, 0x06fa06fe,
  0x07020706, 0x070a070e, 0x07220726, 0x072a072e, 0x07320736, 0x073a073e, 0x07520756, 0x075a075e, 0x07620766, 0x076a076e, 0x00220022, 0x00220022,
  0x00220022, 0x00220022, 0x00220022, 0x048c0490, 0x04940498, 0x049c04e0, 0x04e404e8, 0x04ec04f0, 0x04f404f8, 0x04fc0540, 0x05440548, 0x054c0550,
  0x05540558, 0x055c05a0, 0x05a405a8, 0x05ac05b0, 0x05b405b8, 0x05bc0600, 0x00220022, 0x00220022, 0x00220022, 0x00220022, 0x00220022, 0x0022048e,
  0x04920496, 0x049a049e, 0x04e204e6, 0x04ea04ee, 0x04f204f6, 0x04fa04fe, 0x05420546, 0x054a054e, 0x05520556, 0x055a055e, 0x05a205a6, 0x05aa05ae,
  0x05b205b6, 0x05ba05be, 0x00220022, 0x00220022, 0x00220022, 0x00220022, 0x00220022, 0x002204be, 0x04c204c6, 0x04ca04ce, 0x05120516, 0x051a051e,
  0x05220526, 0x052a052e, 0x05720576, 0x057a057e, 0x05820586, 0x058a058e, 0x05d205d6, 0x05da05de, 0x05e205e6, 0x05ea05ee, 0x00220022, 0x00220022,
  0x00220022, 0x00220022, 0x00220022, 0x002204bc, 0x04c004c4, 0x04c804cc, 0x05100514, 0x0518051c, 0x05200524, 0x0528052c, 0x05700574, 0x0578057c,
  0x05800584, 0x0588058c, 0x05d005d4, 0x05d805dc, 0x05e005e4, 0x05e805ec, 0x00220022, 0x00220022, 0x00220022, 0x00220022, 0x00220022, 0x00220022,
  0x00220022, 0x00220022, 0x00220022, 0x00220022, 0x00220022, 0x00220022, 0x00220022, 0x00220022, 0x00220022, 0x00220022, 0x00220022, 0x00220022,
  0x00220022, 0x00220022, 0x00220022, 0x00220022, 0x00220022, 0x00220022, 0x00220022, 0x00220022, 0x00000022, 0x05400000, 0x00000030, 0x05500010,
  0x00000032, 0x05600020, 0x00000034, 0x05700030, 0x00000036, 0x05800040, 0x00000038, 0x05900050, 0x0000003a, 0x05a00060, 0x0000003c, 0x05b00070,
  0x0000003e, 0x05c00080, 0x00000040, 0x05d00090, 0x00000042, 0x05e000a0, 0x00000044, 0x05f000b0, 0x00000046, 0x060000c0, 0x00000048, 0x061000d0,
  0x0000004a, 0x062000e0, 0x0000004c, 0x063000f0, 0x0000004e, 0x06400100, 0x000001b0, 0x06500110, 0x000001b2, 0x06600120, 0x000001b4, 0x06700130,
  0x000001b6, 0x06800140, 0x000001b8, 0x06900150, 0x000001ba, 0x06a00160, 0x000001bc, 0x06b00170, 0x000001be, 0x06c00180, 0x000001c0, 0x06d00190,
  0x000001c2, 0x06e001a0, 0x000001c4, 0x06f001b0, 0x000001c6, 0x070001c0, 0x000001c8, 0x071001d0, 0x000001ca, 0x072001e0, 0x000001cc, 0x073001f0,
  0x000001ce, 0x07400200, 0x00000300, 0x07500210, 0x00000302, 0x07600220, 0x00000304, 0x07700230, 0x00000306, 0x07800240, 0x00000308, 0x07900250,
  0x0000030a, 0x07a00260, 0x0000030c, 0x07b00270, 0x0000030e, 0x07c00280, 0x00000310, 0x07d00290, 0x00000312, 0x07e002a0, 0x00000314, 0x07f002b0,
  0x00000316, 0x080002c0, 0x00000318, 0x081002d0, 0x0000031a, 0x082002e0, 0x0000031c, 0x083002f0, 0x0000031e, 0x08400300, 0x000003c0, 0x08500310,
  0x000003c2, 0x08600320, 0x000003c4, 0x08700330, 0x000003c6, 0x08800340, 0x000003c8, 0x08900350, 0x000003ca, 0x08a00360, 0x000003cc, 0x08b00370,
  0x000003ce, 0x08c00380, 0x000003d0, 0x08d00390, 0x000003d2, 0x08e003a0, 0x000003d4, 0x08f003b0, 0x000003d6, 0x090003c0, 0x000003d8, 0x091003d0,
  0x000003da, 0x092003e0, 0x000003dc, 0x093003f0, 0x000003de, 0x09400400, 0x00000480, 0x09500410, 0x00000482, 0x09600420, 0x00000484, 0x09700430,
  0x00000486, 0x09800440, 0x00000488, 0x09900450, 0x0000048a, 0x09a00460, 0x00000022, 0x09b00470, 0x00000022, 0x09c00480, 0x00000022, 0x09d00490,
  0x00000022, 0x09e004a0, 0x00000022, 0x09f004b0, 0x00000602, 0x0a0004c0, 0x00000604, 0x0a1004d0, 0x00000606, 0x0a2004e0, 0x00000608, 0x0a3004f0,
  0x0000060a, 0x0a400500, 0x00000022, 0x0a500510, 0x00000022, 0x0a600520, 0x00000022, 0x0a700530, 0x00000022, 0x00000af0, 0x00000022, 0x00000b00,
  0x00000022, 0x00000b10, 0x00000022, 0x00000b20, 0x00000022, 0x00000b30, 0x00000022, 0x00000b40, 0x00000022, 0x00000b50, 0x00000022, 0x00000b60,
  0x00000022, 0x00000b70, 0x00000022, 0x00000bf0, 0x00000022, 0x00000c00, 0x00000022, 0x00000c10, 0x00000022, 0x00000c20, 0x00000022, 0x00000c30,
  0x00000022, 0x00000c40, 0x00000022, 0x00000c50, 0x00000022, 0x00000c60, 0x00000022, 0x00000c70, 0x00000022, 0x00000cb0, 0x00000022, 0x00000cc0,
  0x00000022, 0x00000cd0, 0x00000022, 0x00000ce0, 0x00000022, 0x00000cf0, 0x00000022, 0x00000d70, 0x00000022, 0x00000d80, 0x00000022, 0x00000d90,
  0x00000022, 0x00000da0, 0x00000022, 0x00000db0, 0x00000022, 0x00000e30, 0x00000022, 0x00000e40, 0x00000022, 0x00000e50, 0x00000022, 0x00000e60,
  0x00000022, 0x00000e70, 0x00000022, 0x00000ef0, 0x00000022, 0x00000f00, 0x00000022, 0x00000f10, 0x00000022, 0x00000f20, 0x00000022, 0x00000f30,
  0x00000022, 0x00000000, 0x00000022, 0x00000000, 0x00000022, 0x00000000, 0x00000022, 0x00000000, 0x00000022, 0x00000000, 0x00000022, 0x00000000,
};
constexpr int U_PAD = 28, U_PLANE = (128 + U_PAD) * 16, U_CH = 2 * U_PLANE + 16, SZ_U = 8 * U_CH;
constexpr int TAB_O = 1344, TAB_SZ = 2688, SZ_TAB = 8 * TAB_SZ, TAR_T5 = 512, TAR_SZ = 1280;
constexpr int KT_SZ = 7168, KD_RS = 48, KD_2048 = 32, KD_ZERO = 34, KD_SZ = 40 * KD_RS, SZ_LUT = 3072;
constexpr int WIN_5 = 0, WIN_3 = 3200, WIN_9 = 6400, WIN_7 = 8448, SZ_WIN = 10496;
constexpr int SZ_PKT = SZ_WIN + 8192, SZ_PART = 16384;

struct ASm { uint32_t u, tab, lut, win, part; };

struct cpx { float x, y; };
__device__ __forceinline__ cpx cmul(cpx a, cpx b) { cpx r; r.x = fmaf(a.x, b.x, -a.y * b.y); r.y = fmaf(a.x, b.y, a.y * b.x); return r; }
__device__ __forceinline__ cpx csq(cpx a) { cpx r; r.x = fmaf(a.x, a.x, -a.y * a.y); r.y = (a.x + a.x) * a.y; return r; }
__device__ __forceinline__ cpx zbase(float a2, float th, float Lf) {
  float e = ex2(a2 * Lf);
  float x = th * Lf;
  float k = __fadd_rn(fmaf(x, 0.15915494309f, 12582912.f), -12582912.f);
  float r = fmaf(k, -6.2831854820251465f, x);
  r = fmaf(k, 1.7484555314695172e-7f, r);
  cpx z; z.x = e * __cosf(r); z.y = e * __sinf(r);
  return z;
}
__device__ __forceinline__ void kg_st(uint32_t dst, cpx v0, cpx v1, cpx v2, cpx v3, cpx v4, cpx v5, cpx v6, cpx v7) {
  sts128(dst, pk(v0.x, v1.x), pk(v2.x, v3.x), pk(v4.x, v5.x), pk(v6.x, v7.x));
  sts128(dst + 128, pk(v0.y, v1.y), pk(v2.y, v3.y), pk(v4.y, v5.y), pk(v6.y, v7.y));
}
__device__ __forceinline__ void mma16816(float (&d)[4], uint32_t a0, uint32_t a1, uint32_t a2, uint32_t a3, uint32_t b0, uint32_t b1) {
  asm volatile("mma.sync.aligned.m16n8k16.row.col.f32.bf16.bf16.f32 {%0,%1,%2,%3}, {%4,%5,%6,%7}, {%8,%9}, {%0,%1,%2,%3};"
               : "+f"(d[0]), "+f"(d[1]), "+f"(d[2]), "+f"(d[3]) : "r"(a0), "r"(a1), "r"(a2), "r"(a3), "r"(b0), "r"(b1));
}
__device__ __forceinline__ float bfsel(uint2 v, int j) { uint32_t x = j < 2 ? v.x : v.y; return (j & 1) ? bfhi(x) : bflo(x); }
__device__ __forceinline__ float bfr(float x) { return __bfloat162float(__float2bfloat16_rn(x)); }
__device__ __forceinline__ void a_kgen(const uint8_t* sbase, const int (&soff)[8], int ch, uint32_t kt, uint32_t kd, int lane) {
  uint2 raw[6];
#pragma unroll
  for (int k = 0; k < 6; k++) raw[k] = __ldg(reinterpret_cast<const uint2*>(sbase + ((long long)soff[k] + ch) * 256) + lane);
  const float dsk = __bfloat162float(reinterpret_cast<const bf16*>(sbase + (long long)soff[7] * 256)[ch]);
  const float dt = bfr(expf(__bfloat162float(reinterpret_cast<const bf16*>(sbase + (long long)soff[6] * 256)[ch])));
  float acc[5][4], k2048 = 0.f;
#pragma unroll
  for (int t = 0; t < 5; t++) acc[t][0] = acc[t][1] = acc[t][2] = acc[t][3] = 0.f;
  const uint32_t dst = kt + (lane >> 3) * 256 + (lane & 7) * 16;
  const uint32_t la = kt + (5 + ((lane >> 3) & 1)) * 1024 + (lane >> 4) * 128 + (lane & 7) * 16;
  const uint32_t lb = kt + (lane >> 4) * 1024 + ((lane >> 3) & 1) * 128 + (lane & 7) * 16;
#pragma unroll 1
  for (int j = 0; j < 4; j++) {
    const float a2 = (dt * bfsel(raw[0], j)) * 1.4426950408889634f, th = dt * bfsel(raw[1], j);
    const cpx B = {bfsel(raw[2], j) * dt, bfsel(raw[3], j) * dt}, C = {bfsel(raw[4], j), bfsel(raw[5], j)};
    const cpx z = zbase(a2, th, 128.f);
    {
      cpx m = zbase(a2, -th, 8.f), m2 = csq(m), m4 = csq(m2), one = {1.f, 0.f};
      cpx v3 = cmul(m, m2), v5 = cmul(m, m4), v6 = cmul(m2, m4), v7 = cmul(v3, m4), m8 = csq(m4);
      kg_st(dst + 5 * 1024, one, m, m2, v3, m4, v5, v6, v7);
      kg_st(dst + 6 * 1024, m8, cmul(m, m8), cmul(m2, m8), cmul(v3, m8), cmul(m4, m8), cmul(v5, m8), cmul(v6, m8), cmul(v7, m8));
    }
    uint32_t A[4][4], b0, b1, b2, b3;
    cpx m = zbase(a2, th, 1.f), m2 = csq(m), m4 = csq(m2);
    cpx v0 = cmul(C, B), v1 = cmul(v0, m), v2 = cmul(v0, m2), v3 = cmul(v1, m2);
    cpx v4 = cmul(v0, m4), v5 = cmul(v1, m4), v6 = cmul(v2, m4), v7 = cmul(v3, m4);
    kg_st(dst, v0, v1, v2, v3, v4, v5, v6, v7);
    v0 = cmul(v0, z); v1 = cmul(v1, z); v2 = cmul(v2, z); v3 = cmul(v3, z); v4 = cmul(v4, z); v5 = cmul(v5, z); v6 = cmul(v6, z); v7 = cmul(v7, z);
    kg_st(dst + 1024, v0, v1, v2, v3, v4, v5, v6, v7);
    __syncwarp();
#pragma unroll
    for (int ks = 0; ks < 4; ks++) {
      ldsm4t(la + ks * 256, A[ks][0], A[ks][1], A[ks][2], A[ks][3]);
      ldsm4t(lb + ks * 256, b0, b1, b2, b3);
      mma16816(acc[0], A[ks][0], A[ks][1], A[ks][2], A[ks][3], b0, b1); mma16816(acc[1], A[ks][0], A[ks][1], A[ks][2], A[ks][3], b2, b3);
    }
    v0 = cmul(v0, z); v1 = cmul(v2, z); v2 = cmul(v4, z); v3 = cmul(v6, z);
    v4 = cmul(v0, z); v5 = cmul(v1, z); v6 = cmul(v2, z); v7 = cmul(v3, z);
    kg_st(dst + 2048, v0, v1, v2, v3, v4, v5, v6, v7);
    v0 = cmul(v4, z); v1 = cmul(v6, z); v2 = cmul(v0, z); v3 = cmul(v1, z);
    cpx z2 = csq(z);
    v4 = cmul(v0, z2); v5 = cmul(v1, z2); v6 = cmul(v2, z2); v7 = cmul(v3, z2);
    kg_st(dst + 3072, v0, v1, v2, v3, v4, v5, v6, v7);
    __syncwarp();
#pragma unroll
    for (int ks = 0; ks < 4; ks++) {
      ldsm4t(lb + 2048 + ks * 256, b0, b1, b2, b3);
      mma16816(acc[2], A[ks][0], A[ks][1], A[ks][2], A[ks][3], b0, b1); mma16816(acc[3], A[ks][0], A[ks][1], A[ks][2], A[ks][3], b2, b3);
    }
    cpx z4 = csq(z2);
    v0 = cmul(v0, z4); v1 = cmul(v2, z4); v2 = cmul(v4, z4); v3 = cmul(v6, z4);
    v4 = cmul(v0, z4); v5 = cmul(v1, z4); v6 = cmul(v2, z4); v7 = cmul(v3, z4);
    kg_st(dst + 4096, v0, v1, v2, v3, v4, v5, v6, v7);
    k2048 += fmaf(v4.x, z4.x, -v4.y * z4.y);
    __syncwarp();
#pragma unroll
    for (int ks = 0; ks < 4; ks += 2) {
      ldsm4t(kt + 4096 + ks * 256 + lane * 16, b0, b1, b2, b3);
      mma16816(acc[4], A[ks][0], A[ks][1], A[ks][2], A[ks][3], b0, b1); mma16816(acc[4], A[ks + 1][0], A[ks + 1][1], A[ks + 1][2], A[ks + 1][3], b2, b3);
    }
    __syncwarp();
  }
#pragma unroll
  for (int o = 16; o; o >>= 1) k2048 += __shfl_xor_sync(0xffffffffu, k2048, o);
  if (lane == 0) { acc[0][0] += dsk; sts32(kd + KD_2048, pk(k2048, 0.f)); }
  const uint32_t sd = kd + ((lane >> 4) * 8 + (lane & 7)) * KD_RS + ((lane >> 3) & 1) * 16;
  stsm4t(sd, pk(acc[0][0], acc[0][1]), pk(acc[0][2], acc[0][3]), pk(acc[1][0], acc[1][1]), pk(acc[1][2], acc[1][3]));
  stsm4t(sd + 16 * KD_RS, pk(acc[2][0], acc[2][1]), pk(acc[2][2], acc[2][3]), pk(acc[3][0], acc[3][1]), pk(acc[3][2], acc[3][3]));
  asm volatile("stmatrix.sync.aligned.m8n8.x2.trans.shared.b16 [%0], {%1,%2};" ::"r"(sd + 32 * KD_RS), "r"(pk(acc[4][0], acc[4][1])), "r"(pk(acc[4][2], acc[4][3])) : "memory");
}
__device__ __forceinline__ void a_build(uint4 o, uint2 e, uint32_t kd, uint32_t tab, bool both) {
  uint32_t v0 = lds16(kd + (o.x & 0xffff)), v1 = lds16(kd + (o.x >> 16)), v2 = lds16(kd + (o.y & 0xffff)), v3 = lds16(kd + (o.y >> 16));
  uint32_t v4 = lds16(kd + (o.z & 0xffff)), v5 = lds16(kd + (o.z >> 16)), v6 = lds16(kd + (o.w & 0xffff)), v7 = lds16(kd + (o.w >> 16)), v8 = lds16(kd + e.x);
  sts128(tab + (e.y & 0xffff), __byte_perm(v1, v0, 0x5410), __byte_perm(v3, v2, 0x5410), __byte_perm(v5, v4, 0x5410), __byte_perm(v7, v6, 0x5410));
  if (both) sts128(tab + (e.y >> 16), __byte_perm(v2, v1, 0x5410), __byte_perm(v4, v3, 0x5410), __byte_perm(v6, v5, 0x5410), __byte_perm(v8, v7, 0x5410));
}
#define THROTTLE 0
#define CVTM_ARG
#define CVTM(c)
template <int S0, int S1> __device__ __forceinline__ void cv_load_a(uint32_t base, uint32_t zero, uint32_t (&A)[10][4]) {
#pragma unroll
  for (int s = S0; s < S1; s++) {
    uint32_t a = base + (s < 9 ? s * 128 : 74 * 16);
    A[s][2] = lds32(a); A[s][0] = lds32(a + 16); A[s][1] = lds32(a + 32);
    asm volatile("xor.b32 %0, %1, %2;" : "=r"(A[s][3]) : "r"(A[s][0]), "r"(zero));
  }
}
template <int S0, int S1> __device__ __forceinline__ void cv_dense(uint64_t db, float (&d)[4][16], uint32_t (&A)[10][4]) {
  wg_fence();
#pragma unroll
  for (int s = S0; s < S1; s++) {
#pragma unroll
    for (int G = (s == 9 ? 2 : s == 8); G < 4; G++) {
      if (s == 0) wg_cv_z(d[G], A[0][0], A[0][1], A[0][2], A[0][3], db + 32 * G);
      else wg_cv(d[G], A[s][0], A[s][1], A[s][2], A[s][3], db + 32 * G - (s == 9 ? 64 : 4 * s));
    }
  }
}
__device__ __forceinline__ void cv_load_w(uint32_t win, int w, int lane, uint32_t (&W)[8][4]) {
  int kp = (lane & 7) + ((lane >> 4) << 3), c0 = 2 * w + ((lane >> 3) & 1);
  uint32_t o3 = kp * 128 + ((c0 ^ (kp & 7)) << 4);
  int c2 = 8 * (kp >> 1) + (kp & 1) + c0;
  uint32_t o2 = (c2 >> 3) * 128 + (((c2 & 7) ^ ((c2 >> 2) & 6)) << 4);
  ldsm4t(win + WIN_9 + o3, W[0][0], W[0][1], W[0][2], W[0][3]);
  ldsm4t(win + WIN_7 + o3, W[1][0], W[1][1], W[1][2], W[1][3]);
#pragma unroll
  for (int J = 0; J < 3; J++) {
    ldsm4t(win + WIN_5 + o2 + J * 1024, W[2 + J][0], W[2 + J][1], W[2 + J][2], W[2 + J][3]);
    ldsm4t(win + WIN_3 + o2 + J * 1024, W[5 + J][0], W[5 + J][1], W[5 + J][2], W[5 + J][3]);
  }
}
__device__ __forceinline__ void cv_win_mma(uint32_t tapm, float (&d)[4][16], uint32_t (&W)[8][4]) {
  uint64_t db = mkdesc(tapm, 128, 256, 0);
#define CVW(G, I, OFF) wg_phi_n32(d[G], W[I][0], W[I][1], W[I][2], W[I][3], db + (OFF))
  CVW(2, 0, 0); CVW(3, 0, 64); CVW(1, 2, 256); CVW(2, 1, 128); CVW(3, 1, 192); CVW(1, 5, 384);
  CVW(2, 2, 320); CVW(3, 3, 320); CVW(2, 5, 448); CVW(3, 6, 448); CVW(2, 3, 256); CVW(3, 4, 256); CVW(2, 6, 384); CVW(3, 7, 384);
#undef CVW
  wg_commit();
}
__device__ __forceinline__ uint32_t u_chunk(uint32_t ub, int c8) { return ub + (c8 & 1) * U_PLANE + ((c8 >> 1) + U_PAD) * 16; }
__device__ __forceinline__ void cv_windows(uint32_t ub, int k, uint8_t* dst) {
  uint4 q0 = lds128(u_chunk(ub, k - 3)), q1 = lds128(u_chunk(ub, k - 2)), q2 = lds128(u_chunk(ub, k - 1)), q3 = lds128(u_chunk(ub, k));
  float P[24];
  P[0] = 0.f;
  P[1] = bflo(q0.z); P[2] = P[1] + bfhi(q0.z); P[3] = P[2] + bflo(q0.w); P[4] = P[3] + bfhi(q0.w);
  P[5] = P[4] + bflo(q1.x); P[6] = P[5] + bfhi(q1.x); P[7] = P[6] + bflo(q1.y); P[8] = P[7] + bfhi(q1.y);
  P[9] = P[8] + bflo(q1.z); P[10] = P[9] + bfhi(q1.z); P[11] = P[10] + bflo(q1.w); P[12] = P[11] + bfhi(q1.w);
  P[13] = P[12] + bflo(q2.x); P[14] = P[13] + bfhi(q2.x); P[15] = P[14] + bflo(q2.y); P[16] = P[15] + bfhi(q2.y);
  P[17] = P[16] + bflo(q2.z);
#define WPK(a, b, j) pk(P[(j) + (b)] - P[(j) + (a)], P[(j) + 1 + (b)] - P[(j) + 1 + (a)])
  const uint32_t o3 = (k >> 3) * 128 + (((k & 7) ^ ((k >> 3) & 7)) << 4), o2 = (k >> 3) * 128 + (((k & 7) ^ ((k >> 2) & 6)) << 4);
  *reinterpret_cast<uint4*>(dst + WIN_5 + o2) = make_uint4(WPK(2, 7, 0), WPK(2, 7, 2), WPK(2, 7, 4), WPK(2, 7, 6));
  *reinterpret_cast<uint4*>(dst + WIN_3 + o2) = make_uint4(WPK(7, 10, 0), WPK(7, 10, 2), WPK(7, 10, 4), WPK(7, 10, 6));
  if (k < 128) {
    P[18] = P[17] + bfhi(q2.z); P[19] = P[18] + bflo(q2.w); P[20] = P[19] + bfhi(q2.w);
    P[21] = P[20] + bflo(q3.x); P[22] = P[21] + bfhi(q3.x); P[23] = P[22] + bflo(q3.y);
    *reinterpret_cast<uint4*>(dst + WIN_9 + o3) = make_uint4(WPK(0, 9, 0), WPK(0, 9, 2), WPK(0, 9, 4), WPK(0, 9, 6));
    *reinterpret_cast<uint4*>(dst + WIN_7 + o3) = make_uint4(WPK(9, 16, 0), WPK(9, 16, 2), WPK(9, 16, 4), WPK(9, 16, 6));
  }
#undef WPK
}
__device__ __forceinline__ void cv_tapm(uint32_t tar, int t, uint8_t* dst) {
  int kp = t & 15, nu = t >> 4;
  uint32_t s3 = tar + (8 * nu - 4 * kp + 60) * 2, s2 = tar + TAR_T5 + (kp & 1) * 192 + (8 * nu - 4 * (kp >> 1) + 28) * 2;
  uint2 a0 = lds64(s3), b0 = lds64(s3 + 8), a1 = lds64(s3 + 256), b1 = lds64(s3 + 264), a2 = lds64(s2), b2 = lds64(s2 + 8), a3 = lds64(s2 + 384), b3 = lds64(s2 + 392);
  uint4* d = reinterpret_cast<uint4*>(dst + SZ_WIN) + t;
  d[0] = make_uint4(a0.x, a0.y, b0.x, b0.y); d[128] = make_uint4(a1.x, a1.y, b1.x, b1.y);
  d[256] = make_uint4(a2.x, a2.y, b2.x, b2.y); d[384] = make_uint4(a3.x, a3.y, b3.x, b3.y);
}
__device__ __forceinline__ void cv_st_part(const ASm& S, int w, int lane, uint32_t (&P)[32]) {
  uint32_t a = S.part + w * 4096 + ((lane >> 3) & 1) * 2048 + ((lane >> 4) * 8 + (lane & 7)) * 16;
#pragma unroll
  for (int j = 0; j < 8; j++) stsm4t(a + j * 256, P[4 * j], P[4 * j + 1], P[4 * j + 2], P[4 * j + 3]);
}
__device__ __forceinline__ void cv_red_ld(const ASm& S, int tid, int h, uint4 (&p)[4]) {
  uint32_t a = S.part + h * 2048 + tid * 16;
  uint4 z = make_uint4(0, 0, 0, 0);
  p[0] = lds128(a); p[1] = tid >= 1 ? lds128(a + 4096 - 16) : z; p[2] = tid >= 2 ? lds128(a + 8192 - 32) : z; p[3] = tid >= 3 ? lds128(a + 12288 - 48) : z;
}
__device__ __forceinline__ uint4 cv_red_add(const uint4 (&p)[4]) {
  return make_uint4(hadd2(hadd2(p[0].x, p[1].x), hadd2(p[2].x, p[3].x)), hadd2(hadd2(p[0].y, p[1].y), hadd2(p[2].y, p[3].y)),
                    hadd2(hadd2(p[0].z, p[1].z), hadd2(p[2].z, p[3].z)), hadd2(hadd2(p[0].w, p[1].w), hadd2(p[2].w, p[3].w)));
}
__device__ __forceinline__ void stg128(uint4* p, uint4 v) { asm volatile("st.global.v4.u32 [%0], {%1,%2,%3,%4};" ::"l"(p), "r"(v.x), "r"(v.y), "r"(v.z), "r"(v.w) : "memory"); }
__device__ __forceinline__ void cv_run(const ASm& S, int tid_, int w, bf16* aT, int barid, uint32_t wbar, const uint8_t* gpkt CVTM_ARG) {
  const int tid = __shfl_sync(0xffffffffu, tid_, tid_ & 31), lane = tid & 31;
  const int g = lane >> 2, dl = g - 2 * (lane & 3);
  uint32_t abase = S.tab + ((g & 1) ? TAB_O : 0) + (((dl - (g & 1)) >> 1) + 7) * 4 + (2 * w - 1) * 16;
  float d[4][16];
  uint4* dst = reinterpret_cast<uint4*>(aT) + tid * 2;
#pragma unroll
  for (int j = 0; j < 64; j++) d[j >> 4][j & 15] = 0.f;
#pragma unroll 1
  for (int c = 0; c < 8; c++) {
    CVTM(c);
    const uint32_t pkt = S.win + (c & 1) * SZ_PKT;
    const uint64_t db = mkdesc(S.u + c * U_CH, U_PLANE, 128, 0) + U_PAD;
    uint32_t W[8][4], A[10][4], P[32];
    if (w == 0 && elect_one()) {
      if (c >= 1 && c < 7) { uint32_t b = wbar + 8 * ((c + 1) & 1); mbar_expect_tx(b, SZ_PKT); bulk_g2s(S.win + ((c + 1) & 1) * SZ_PKT, gpkt + (c - 1) * SZ_PKT, SZ_PKT, b); }
      if (c == 4) mbar_arrive(wbar + 16);
    }
    mbar_wait(wbar + 8 * (c & 1), ((c >> 1) & 1) ^ 1);
    cv_load_w(pkt, w, lane, W);
    cv_load_a<0, 10>(abase, tid >> 7, A);
    abase += TAB_SZ;
#pragma unroll
    for (int j = 0; j < 32; j++) P[j] = pk(d[j >> 3][(2 * j) & 15], d[j >> 3][(2 * j + 1) & 15]);
    cv_st_part(S, w, lane, P);
    bar_sync(barid, 128);
    uint4 p0[4], p1[4];
    cv_red_ld(S, tid, 0, p0);
    cv_red_ld(S, tid, 1, p1);
    stg128(dst, cv_red_add(p0));
    stg128(dst + 1, cv_red_add(p1));
    if (c > 0) dst += 256;
    cv_dense<0, 10>(db, d, A);
    cv_win_mma(pkt + SZ_WIN, d, W);
    wg_wait<0>();
  }
  uint32_t P[32];
#pragma unroll
  for (int j = 0; j < 32; j++) P[j] = pk(d[j >> 3][(2 * j) & 15], d[j >> 3][(2 * j + 1) & 15]);
  cv_st_part(S, w, lane, P);
  bar_sync(barid, 128);
  uint4 p[4];
  cv_red_ld(S, tid, 0, p); stg128(dst, cv_red_add(p));
  cv_red_ld(S, tid, 1, p); stg128(dst + 1, cv_red_add(p));
}
struct SmA { uint32_t x[8]; float cp[2], cn[2]; };
struct SmB { float ep[16], en[16], sp[2], sn[2]; };
constexpr float L2E = 1.4426950408889634f;
__device__ __forceinline__ void sm_a(const float (&p)[16], SmA& a) {
  uint32_t m[2];
#pragma unroll
  for (int r = 0; r < 2; r++) {
#pragma unroll
    for (int t = 0; t < 4; t++) a.x[4 * r + t] = pk(p[4 * t + 2 * r], p[4 * t + 2 * r + 1]);
    uint32_t mx = hmax2(hmax2(a.x[4 * r], a.x[4 * r + 1]), hmax2(a.x[4 * r + 2], a.x[4 * r + 3]));
    uint32_t mn = hmin2(hmin2(a.x[4 * r], a.x[4 * r + 1]), hmin2(a.x[4 * r + 2], a.x[4 * r + 3]));
    m[r] = hmax2(__byte_perm(mx, mn, 0x5410) ^ 0x80000000u, __byte_perm(mx, mn, 0x7632) ^ 0x80000000u);
  }
#pragma unroll
  for (int o = 1; o <= 2; o *= 2) {
    uint32_t t0 = __shfl_xor_sync(0xffffffffu, m[0], o), t1 = __shfl_xor_sync(0xffffffffu, m[1], o);
    m[0] = hmax2(m[0], t0); m[1] = hmax2(m[1], t1);
  }
#pragma unroll
  for (int r = 0; r < 2; r++) { a.cp[r] = -L2E * bflo(m[r]); a.cn[r] = -L2E * bfhi(m[r]); }
}
__device__ __forceinline__ void sm_b(const SmA& a, SmB& b) {
#pragma unroll
  for (int r = 0; r < 2; r++) {
#pragma unroll
    for (int t = 0; t < 4; t++) {
      float v0 = bflo(a.x[4 * r + t]), v1 = bfhi(a.x[4 * r + t]);
      b.ep[8 * r + 2 * t] = ex2(fmaf(v0, L2E, a.cp[r])); b.ep[8 * r + 2 * t + 1] = ex2(fmaf(v1, L2E, a.cp[r]));
      b.en[8 * r + 2 * t] = ex2(fmaf(v0, -L2E, a.cn[r])); b.en[8 * r + 2 * t + 1] = ex2(fmaf(v1, -L2E, a.cn[r]));
    }
    const float *e = b.ep + 8 * r, *f = b.en + 8 * r;
    b.sp[r] = ((e[0] + e[1]) + (e[2] + e[3])) + ((e[4] + e[5]) + (e[6] + e[7]));
    b.sn[r] = ((f[0] + f[1]) + (f[2] + f[3])) + ((f[4] + f[5]) + (f[6] + f[7]));
  }
}
__device__ __forceinline__ void sm_c(SmB& b, uint32_t (&o)[16]) {
#pragma unroll
  for (int s = 1; s <= 2; s *= 2) {
    float t0 = __shfl_xor_sync(0xffffffffu, b.sp[0], s), t1 = __shfl_xor_sync(0xffffffffu, b.sn[0], s);
    float t2 = __shfl_xor_sync(0xffffffffu, b.sp[1], s), t3 = __shfl_xor_sync(0xffffffffu, b.sn[1], s);
    b.sp[0] += t0; b.sn[0] += t1; b.sp[1] += t2; b.sn[1] += t3;
  }
#pragma unroll
  for (int r = 0; r < 2; r++) {
    const float ip = rcp(b.sp[r]), in = rcp(b.sn[r]);
#pragma unroll
    for (int t = 0; t < 4; t++) {
      o[2 * t + r] = pk(b.ep[8 * r + 2 * t] * ip, b.ep[8 * r + 2 * t + 1] * ip);
      o[8 + 2 * t + r] = pk(b.en[8 * r + 2 * t] * in, b.en[8 * r + 2 * t + 1] * in);
    }
  }
}
__device__ __forceinline__ void phi_gemm(float (&p)[16], const uint32_t (&a)[8], uint64_t db) {
  wg_fence();
  wg_phi_n32_z(p, a[0], a[1], a[2], a[3], db);
  wg_phi_n32(p, a[4], a[5], a[6], a[7], db + 64);
  wg_commit();
}
__device__ __forceinline__ void wait_flag(const uint32_t* f, uint32_t target) {
  asm volatile("{.reg .pred p; .reg .u32 cnt, v; mov.u32 cnt, 0;\nLW: ld.relaxed.gpu.global.u32 v, [%0]; sub.u32 v, v, %1; setp.ge.s32 p, v, 0; @p bra LD; add.u32 cnt, cnt, 1; setp.lt.u32 p, cnt, 0x200000; @p bra LW; trap;\nLD: }" ::"l"(f), "r"(target) : "memory");
}
__device__ bf16 g_aT[1024 * 2048];
__device__ bf16 g_o[2048 * 1024];
__device__ float g_kv[2][32 * 64 * 40];
__device__ __align__(16) uint8_t g_win[128 * 6 * SZ_PKT];
__device__ __align__(16) float2 g_gate[2048];
__device__ uint32_t g_epoch[128 * 8];
__device__ uint32_t g_kvflag[32 * 8], g_oflag[16 * 32], g_aflag[128], g_gflag[8 * 8];
#define TM(i)

#define NOJOB 0
constexpr int NST = 4, ST_A = 16384, ST_SZ = 28672;
constexpr int OFF_U = NST * ST_SZ, OFF_WIN = OFF_U + SZ_U, OFF_PART = OFF_WIN + 2 * SZ_PKT, OFF_TAB = OFF_PART + SZ_PART;
constexpr int OFF_BAR = OFF_TAB + SZ_TAB, SMEM_TOTAL = OFF_BAR + 256;
constexpr int OFF_KT = OFF_U, OFF_KD = OFF_KT + 8 * KT_SZ, OFF_LUT = OFF_KD + 8 * KD_SZ, OFF_URAW = OFF_BAR - 32768;
constexpr int OFF_TAR = OFF_PART;
static_assert(OFF_LUT + SZ_LUT <= OFF_URAW && OFF_LUT + SZ_LUT <= OFF_TAR, "aliases");
static_assert(SMEM_TOTAL <= 232448, "smem");
static_assert(OFF_WIN % 128 == 0 && OFF_KD % 16 == 0 && OFF_LUT % 16 == 0 && OFF_TAB % 16 == 0 && OFF_BAR % 8 == 0, "align");
constexpr int OFF_V = 0, OFF_WPHI = 32768, OFF_ONES = OFF_WPHI + 4096, OFF_KVB = OFF_ONES + 1024, OFF_PHI = 49152;
__device__ __forceinline__ uint32_t a2_slot(int i) { return i == 0 ? 32768u : 32768u + i * 32768u - (i == 3 ? 16384u : 0u); }
__device__ __forceinline__ uint32_t b2_slot(int i) { return i < 2 ? i * 16384u : i * 32768u - 16384u; }
constexpr int OFF_AT = OFF_U + 16384, OFF_OUT = OFF_AT + 32768, OFF_GT = OFF_OUT + 32768;
static_assert(OFF_U == 7 * 16384 && 4 * U_CH >= 16384 && OFF_GT + 1024 <= OFF_BAR, "phase-2 slots");
static_assert(OFF_KVB + 10240 <= OFF_PHI && OFF_WPHI >= ST_SZ && OFF_PHI <= 2 * ST_SZ, "consumer regions");
enum { B_FULL = 0, B_EMPTY = 4, B_LUT = 8, B_KG = 9, B_WPHI = 10, B_FULL2 = 11, B_EMPTY2 = 15, B_AT = 19, B_WIN = 20, B_CV4 = 22, B_NUM = 23 };
enum { NB_FILL = 1, NB_WG0 = 2, NB_WG1 = 3, NB_CONS = 4, NB_F3 = 5, NB_INIT = 6 };

struct Params {
  const uint8_t* sbase; int soff[8];
  const bf16 *x, *gw;
  bf16* aT; float* kv; float2* gate; uint8_t* win; const uint32_t* lut;
  uint32_t *epoch, *kvflag, *oflag, *aflag, *gflag;
};

__global__ void __launch_bounds__(384, 1)
fused_kernel(const Params P, const __grid_constant__ CUtensorMap mx, const __grid_constant__ CUtensorMap mw, const __grid_constant__ CUtensorMap mphi,
             const __grid_constant__ CUtensorMap mu, const __grid_constant__ CUtensorMap moa, const __grid_constant__ CUtensorMap mwo, const __grid_constant__ CUtensorMap mat,
             const __grid_constant__ CUtensorMap mout) {
  extern __shared__ __align__(1024) uint8_t smem[];
  const uint32_t sb = smem_u32(smem);
  const uint32_t bars = sb + OFF_BAR;
  const int wid = __shfl_sync(0xffffffffu, threadIdx.x >> 5, 0);
  const int tid = threadIdx.x & 127, wg = wid >> 2, w = wid & 3, lane = tid & 31;
  const int rb = blockIdx.x >> 4, hp = blockIdx.x & 15;
  const int r128 = 2 * rb + (hp >> 3), cb = hp & 7;
  TM(0);
  if (wg == 2) {
    if (tid == 96) {
      if (sb & 1023) __trap();
      for (int i = 0; i < NST; i++) { mbar_init(bars + 8 * (B_FULL + i), 1); mbar_init(bars + 8 * (B_EMPTY + i), 2); }
      mbar_init(bars + 8 * B_LUT, 1); mbar_init(bars + 8 * B_KG, 8); mbar_init(bars + 8 * B_WIN, 1); mbar_init(bars + 8 * B_WIN + 8, 1);
      mbar_init(bars + 8 * B_WPHI, 1); mbar_init(bars + 8 * B_CV4, 1); mbar_init(bars + 8 * B_AT, 1);
      for (int i = 0; i < 4; i++) { mbar_init(bars + 8 * (B_FULL2 + i), 2); mbar_init(bars + 8 * (B_EMPTY2 + i), 1); }
      asm volatile("fence.mbarrier_init.release.cluster;" ::: "memory");
      fence_async_smem();
    }
    const uint32_t epoch = P.epoch[blockIdx.x * 8];
    if (tid == 0) sts32(bars + 8 * B_NUM, epoch);
    bar_sync(NB_FILL, 128);
    bar_arrive(NB_INIT, 384);
    asm volatile("setmaxnreg.dec.sync.aligned.u32 56;");
    ASm S;
    S.u = sb + OFF_U; S.tab = sb + OFF_TAB; S.lut = sb + OFF_LUT; S.win = sb + OFF_WIN; S.part = sb + OFF_PART;
    const int ch0 = blockIdx.x * 8;
    uint8_t* gwin = P.win + (size_t)blockIdx.x * 6 * SZ_PKT;
    if (w == 3) {
      if (elect_one()) {
        for (int kb = 0; kb < 32; kb++) {
          int st = kb & 3;
          if (kb == NST) {
            mbar_expect_tx(bars + 8 * B_LUT, SZ_LUT + 32768);
            bulk_g2s(S.lut, P.lut, SZ_LUT, bars + 8 * B_LUT);
            for (int j = 0; j < 8; j++) tma_2d(sb + OFF_URAW + j * 4096, &mu, ch0, j * 256, bars + 8 * B_LUT);
            prefetch_map(&mphi); prefetch_map(&moa); prefetch_map(&mwo); prefetch_map(&mat); prefetch_map(&mout);
          }
          if (kb >= NST) mbar_wait(bars + 8 * (B_EMPTY + st), ((kb >> 2) - 1) & 1);
          uint32_t fb = bars + 8 * (B_FULL + st);
          mbar_expect_tx(fb, ST_SZ);
          tma_2d(sb + st * ST_SZ, &mx, kb * 32, rb * 256, fb);
          tma_3d(sb + st * ST_SZ + ST_A, &mw, hp * 64, kb * 32, 0, fb);
        }
        mbar_wait(bars + 8 * (B_EMPTY + 1), 1);
        mbar_expect_tx(bars + 8 * B_WPHI, 4096);
        tma_2d(sb + OFF_WPHI, &mphi, 0, hp * 64, bars + 8 * B_WPHI);
      }
      __syncwarp();
    } else {
      {
        float* z = (P.kv + ((epoch + 1) & 1) * 81920) + (hp * 2 * 64 + rb * 8) * 40;
        for (int i = tid; i < 160; i += 96) *reinterpret_cast<float4*>(z + (i / 80) * 2560 + (i % 80) * 4) = make_float4(0.f, 0.f, 0.f, 0.f);
      }
      mbar_wait(bars + 8 * B_LUT, 0);
      const uint4 lo0 = lds128(S.lut + tid * 16), lo1 = lds128(S.lut + (96 + lane) * 16);
      const uint2 le0 = lds64(S.lut + 2048 + tid * 8), le1 = lds64(S.lut + 2048 + (96 + lane) * 8);
      mbar_wait(bars + 8 * B_KG, 0);
      bar_sync(NB_F3, 96);
      TM(1);
      {
        const uint32_t dst = S.u + (lane & 7) * U_CH + ((lane >> 3) & 1) * U_PLANE + ((lane >> 4) + U_PAD) * 16;
#pragma unroll 1
        for (int j = 2 * w; j < 64; j += 6) {
          uint32_t r0, r1, r2, r3, r4, r5, r6, r7;
          ldsm4t(sb + OFF_URAW + (j * 32 + lane) * 16, r0, r1, r2, r3);
          ldsm4t(sb + OFF_URAW + (j * 32 + 32 + lane) * 16, r4, r5, r6, r7);
          stsm4(dst + j * 32, r0, r1, r2, r3);
          stsm4(dst + j * 32 + 32, r4, r5, r6, r7);
        }
        if (lane < U_PAD) for (int i = w; i < 16; i += 3) sts128(S.u + (i >> 1) * U_CH + (i & 1) * U_PLANE + lane * 16, 0, 0, 0, 0);
      }
      bar_sync(NB_F3, 96);
      for (int i = tid; i < 8 * TAR_SZ / 16; i += 96) sts128(sb + OFF_TAR + i * 16, 0, 0, 0, 0);
      bar_sync(NB_F3, 96);
#pragma unroll 2
      for (int c = 0; c < 8; c++) a_build(lo0, le0, sb + OFF_KD + c * KD_SZ, tid < 84 ? S.tab + c * TAB_SZ : sb + OFF_TAR - TAB_SZ + c * TAR_SZ, tid < 84);
      if (lane < 26) for (int c = w; c < 8; c += 3) a_build(lo1, le1, sb + OFF_KD + c * KD_SZ, sb + OFF_TAR - TAB_SZ + c * TAR_SZ, false);
      bar_sync(NB_F3, 96);
      TM(2);
#pragma unroll 1
      for (int i = 0; i < 16; i++) {
        int c = i >> 1;
        cv_windows(S.u + c * U_CH, tid + (i & 1) * 96, c < 2 ? smem + OFF_WIN + c * SZ_PKT : gwin + (c - 2) * SZ_PKT);
      }
#pragma unroll 1
      for (int i = tid; i < 1024; i += 96) {
        int c = i >> 7;
        cv_tapm(sb + OFF_TAR + c * TAR_SZ, i & 127, c < 2 ? smem + OFF_WIN + c * SZ_PKT : gwin + (c - 2) * SZ_PKT);
      }
      if (tid < 8) cv_windows(S.u + tid * U_CH, 192, tid < 2 ? smem + OFF_WIN + tid * SZ_PKT : gwin + (tid - 2) * SZ_PKT);
      __threadfence();
      asm volatile("fence.proxy.async;" ::: "memory");
      TM(7);
      const uint4* gw = reinterpret_cast<const uint4*>(P.gw) + (lane & 15);
#pragma unroll 1
      for (int r = 2 * w; r < 16; r += 6) {
        int row = rb * 256 + hp * 16 + r + (lane >> 4);
        const uint4* xr = reinterpret_cast<const uint4*>(P.x + (size_t)row * 1024) + (lane & 15);
        float s = 0.f;
#pragma unroll
        for (int h = 0; h < 2; h++) {
          uint4 x[4], wv[4];
#pragma unroll
          for (int j = 0; j < 4; j++) { x[j] = __ldg(xr + 64 * h + 16 * j); wv[j] = __ldg(gw + 64 * h + 16 * j); }
#pragma unroll
          for (int j = 0; j < 4; j++) {
            uint32_t q0 = hmul2(x[j].x, wv[j].x), q1 = hmul2(x[j].y, wv[j].y), q2 = hmul2(x[j].z, wv[j].z), q3 = hmul2(x[j].w, wv[j].w);
            s += ((bflo(q0) + bfhi(q0)) + (bflo(q1) + bfhi(q1))) + ((bflo(q2) + bfhi(q2)) + (bflo(q3) + bfhi(q3)));
          }
        }
#pragma unroll
        for (int o = 8; o; o >>= 1) s += __shfl_xor_sync(0xffffffffu, s, o);
        float g = bfr(1.f / (1.f + __expf(-bfr(s))));
        if ((lane & 15) == 0) P.gate[row] = make_float2(g, bfr(1.f - g));
      }
      __syncwarp();
      if (lane == 0) red_rel(&P.gflag[rb * 8], 1);
      __syncwarp();
      TM(8);
    }
    bar_sync(NB_FILL, 128);
    TM(3);
    asm volatile("setmaxnreg.inc.sync.aligned.u32 168;");
    TM(4);
    cv_run(S, tid, w, P.aT + (size_t)ch0 * 2048, NB_FILL, bars + 8 * B_WIN, gwin
    );
    TM(5);
    bar_sync(NB_FILL, 128);
    if (w == 3) {
      if (lane == 0) asm volatile("st.release.gpu.global.u32 [%0], %1;" ::"l"(&P.aflag[blockIdx.x]), "r"(epoch + 1) : "memory");
      if (lane < 17) wait_flag(lane < 16 ? &P.aflag[cb * 16 + lane] : &P.gflag[rb * 8], lane < 16 ? epoch + 1 : 48 * (epoch + 1));
      __syncwarp();
      if (elect_one()) {
        fence_async_smem();
        mbar_expect_tx(bars + 8 * B_AT, 32768 + 1024);
        bulk_g2s(sb + OFF_GT, P.gate + r128 * 128, 1024, bars + 8 * B_AT);
        tma_2d(sb + OFF_AT, &mat, r128 * 128, cb * 128, bars + 8 * B_AT);
        tma_2d(sb + OFF_AT + 16384, &mat, r128 * 128 + 64, cb * 128, bars + 8 * B_AT);
        P.epoch[blockIdx.x * 8] = epoch + 1;
      }
    }
    TM(6);
  } else {
    a_kgen(P.sbase, P.soff, blockIdx.x * 8 + wid, sb + OFF_KT + wid * KT_SZ, sb + OFF_KD + wid * KD_SZ, lane);
    bar_sync(NB_INIT, 384);
    if (lane == 0) mbar_arrive(bars + 8 * B_KG);
    TM(19);
    asm volatile("setmaxnreg.inc.sync.aligned.u32 224;");
    uint32_t qf[2][2][8], kf[2][2][8];
    int tx;
    {
      float acc[2][96];
#pragma unroll 1
      for (int kb = 0; kb < 32; kb++) {
        int st = kb & 3;
        mbar_wait(bars + 8 * (B_FULL + st), (kb >> 2) & 1);

        uint64_t da = mkdesc(sb + st * ST_SZ + wg * 8192, 16, 512, 2), db = mkdesc(sb + st * ST_SZ + ST_A, 4096, 1024, 1);
        wg_fence();
#pragma unroll
        for (int k = 0; k < 2; k++) {
          wg_p1_n192(acc[0], da + k * 2, db + k * 128, (kb | k) != 0);
          wg_p1_n192(acc[1], da + k * 2 + 256, db + k * 128, (kb | k) != 0);
        }
        wg_commit();
        if (kb > 0) { wg_wait<1>(); if (tid == 0) mbar_arrive(bars + 8 * (B_EMPTY + ((kb - 1) & 3))); }
      }
      wg_wait<0>();
      TM(2);
      asm volatile("mov.u32 %0, %%tid.x;" : "=r"(tx));
      const int lane = tx & 31;
      uint32_t vf[2][2][8];
#pragma unroll
      for (int mb = 0; mb < 2; mb++)
#pragma unroll
        for (int h = 0; h < 2; h++)
#pragma unroll
          for (int i = 0; i < 8; i++) {
            qf[h][mb][i] = pk(acc[mb][16 * h + 2 * i], acc[mb][16 * h + 2 * i + 1]);
            kf[h][mb][i] = pk(acc[mb][32 + 16 * h + 2 * i], acc[mb][32 + 16 * h + 2 * i + 1]);
            vf[h][mb][i] = pk(acc[mb][64 + 16 * h + 2 * i], acc[mb][64 + 16 * h + 2 * i + 1]);
          }
      bar_sync(NB_CONS, 256);
      TM(3);
#pragma unroll
      for (int mb = 0; mb < 2; mb++) {
        int row = wg * 128 + mb * 64 + w * 16 + (lane & 15);
#pragma unroll
        for (int h = 0; h < 2; h++)
#pragma unroll
          for (int kk = 0; kk < 2; kk++)
            stsm4(sb + OFF_V + h * 16384 + row * 64 + (((2 * kk + (lane >> 4)) ^ ((row >> 1) & 3)) << 4), vf[h][mb][4 * kk], vf[h][mb][4 * kk + 1], vf[h][mb][4 * kk + 2], vf[h][mb][4 * kk + 3]);
      }
    }
    const int tid = tx & 127, lane = tid & 31, g = lane >> 2, q = lane & 3;
    const uint32_t epoch = lds32(bars + 8 * B_NUM);
    if (wg == 0 && tid < 64) sts128(sb + OFF_ONES + tid * 16, 0x3f803f80u, 0x3f803f80u, 0x3f803f80u, 0x3f803f80u);
    asm volatile("setmaxnreg.dec.sync.aligned.u32 168;");
    mbar_wait(bars + 8 * B_WPHI, 0);
    TM(4);
    const uint64_t dphi = mkdesc(sb + OFF_WPHI, 16, 512, 2);
    float* kvg = P.kv + (epoch & 1) * 81920 + hp * 5120;
    const int srow = w * 16 + (lane & 15);
    float pa[16], pb[16];
    SmA sa;
    SmB sx;
    uint32_t pq[2][2][16];
    {
      uint32_t ph[16];
      float kv[20];
      const uint32_t pst = sb + OFF_PHI + (wg * 128 + srow) * 128;
      auto st_phi = [&](int h, int mb) {
#pragma unroll
        for (int j = 0; j < 4; j++)
          stsm4(pst + h * 32768 + mb * 8192 + (((2 * j + (lane >> 4)) ^ (lane & 7)) << 4), ph[4 * j], ph[4 * j + 1], ph[4 * j + 2], ph[4 * j + 3]);
      };
      phi_gemm(pa, kf[0][0], dphi);
      phi_gemm(pb, kf[0][1], dphi);
      wg_wait<1>();
      sm_a(pa, sa); phi_gemm(pa, kf[1][0], dphi + 128);
      sm_b(sa, sx); wg_wait<1>(); sm_a(pb, sa); phi_gemm(pb, kf[1][1], dphi + 128); sm_c(sx, ph); st_phi(0, 0);
      sm_b(sa, sx); wg_wait<1>(); sm_a(pa, sa); phi_gemm(pa, qf[0][0], dphi); sm_c(sx, ph); st_phi(0, 1);
      TM(5);
      sm_b(sa, sx); wg_wait<1>(); sm_a(pb, sa); phi_gemm(pb, qf[0][1], dphi); sm_c(sx, ph); st_phi(1, 0);
      sm_b(sa, sx); wg_wait<1>(); sm_a(pa, sa); phi_gemm(pa, qf[1][0], dphi + 128); sm_c(sx, ph); st_phi(1, 1);
      fence_async_smem();
      bar_sync(NB_CONS, 256);
      TM(6);
      sm_b(sa, sx);
      const uint64_t da = mkdesc(sb + OFF_PHI + wg * 32768, 16, 1024, 1);
      const uint64_t db = mkdesc(sb + OFF_V + wg * 16384, OFF_ONES - OFF_V - wg * 16384, 512, 2);
      wg_fence();
#pragma unroll
      for (int ks = 0; ks < 16; ks++) wg_kv_n40(kv, da + ks * 128, db - (uint64_t)ks * 0x3FFFC0u, ks != 0);
      wg_commit();
      wg_wait<2>(); sm_a(pb, sa); sm_c(sx, pq[0][0]);
      wg_wait<0>();
      phi_gemm(pb, qf[1][1], dphi + 128);
      const uint32_t st = sb + OFF_PHI + wg * 32768, a = st + (w * 16 + g) * 160 + q * 8;
#pragma unroll
      for (int j = 0; j < 5; j++) {
        sts64(a + j * 32, __float_as_uint(kv[4 * j]), __float_as_uint(kv[4 * j + 1]));
        sts64(a + j * 32 + 1280, __float_as_uint(kv[4 * j + 2]), __float_as_uint(kv[4 * j + 3]));
      }
      fence_async_smem();
      bar_sync(NB_WG0 + wg, 128);
      if (w == wg && elect_one()) {
        asm volatile("cp.reduce.async.bulk.global.shared::cta.bulk_group.add.f32 [%0], [%1], %2;" ::"l"(kvg + wg * 2560), "r"(st), "r"(10240) : "memory");
        bulk_commit();
      }
      if (w == 2 + wg && elect_one()) {
        uint32_t fb = bars + 8 * (B_FULL2 + wg);
        mbar_expect_tx(fb, 16384); tma_3d(sb + b2_slot(wg), &mwo, 0, wg * 64, 2 * cb, fb);
      }
      __syncwarp();
      TM(7);
    }
    sm_b(sa, sx); sm_a(pa, sa); sm_c(sx, pq[0][1]);
    sm_b(sa, sx); wg_wait<0>(); sm_a(pb, sa); sm_c(sx, pq[1][0]);
    if (w == wg && elect_one()) { bulk_wait0(); red_rlx(&P.kvflag[(hp * 2 + wg) * 8], 1); }
    __syncwarp();
    TM(8);
    sm_b(sa, sx); sm_c(sx, pq[1][1]);
    TM(9);
    wait_flag(&P.kvflag[(hp * 2 + (lane & 1)) * 8], 8 * (epoch + 1));
    __syncwarp();
    TM(10);
    {
      float4 v[5];
#pragma unroll
      for (int i = 0; i < 5; i++) v[i] = __ldcg(reinterpret_cast<const float4*>(kvg) + tx + 256 * i);
#pragma unroll
      for (int i = 0; i < 5; i++) {
        const int c = tx + 256 * i, f = (c * 6554) >> 16, j = c - f * 10;
        sts64(sb + OFF_KVB + (f >> 6) * 5120 + (j >> 1) * 1024 + (f & 63) * 16 + (j & 1) * 8, pk(v[i].x, v[i].y), pk(v[i].z, v[i].w));
      }
    }
    fence_async_smem();
    bar_sync(NB_CONS, 256);
    TM(11);
    {
      float o[2][2][20];
      const uint64_t db = mkdesc(sb + OFF_KVB, 128, 1024, 0);
#pragma unroll
      for (int h = 0; h < 2; h++) {
        if (h == 1) wg_wait<0>();
        wg_fence();
#pragma unroll
        for (int mb = 0; mb < 2; mb++) {
          wg_o_n40_z(o[h][mb], pq[h][mb][0], pq[h][mb][1], pq[h][mb][2], pq[h][mb][3], db + h * 320);
#pragma unroll
          for (int kk = 1; kk < 4; kk++) wg_o_n40(o[h][mb], pq[h][mb][4 * kk], pq[h][mb][4 * kk + 1], pq[h][mb][4 * kk + 2], pq[h][mb][4 * kk + 3], db + h * 320 + kk * 16);
        }
        wg_commit();
      }
      const uint32_t ost = sb + OFF_PHI + 16384 + wg * 32768;
#pragma unroll
      for (int h = 0; h < 2; h++) {
        if (h == 1) wg_wait<0>();
#pragma unroll
        for (int mb = 0; mb < 2; mb++) {
          const float i0 = rcp(o[h][mb][16] + 1e-6f), i1 = rcp(o[h][mb][18] + 1e-6f);
#pragma unroll
          for (int kk = 0; kk < 2; kk++) {
            const float* a = &o[h][mb][8 * kk];
            stsm4(ost + (mb * 64 + srow) * 128 + (((4 * h + 2 * kk + (lane >> 4)) ^ (lane & 7)) << 4), pk(a[0] * i0, a[1] * i0), pk(a[2] * i1, a[3] * i1), pk(a[4] * i0, a[5] * i0), pk(a[6] * i1, a[7] * i1));
          }
        }
      }
      fence_async_smem();
      bar_sync(NB_WG0 + wg, 128);
      TM(12);
      if (w == 0 && elect_one()) {
        tma_st_2d(&moa, hp * 64, rb * 256 + wg * 128, ost);
        bulk_commit();
        bulk_wait0();
        st_rlx(&P.oflag[(rb * 2 + wg) * 32 + hp], epoch + 1);
      }
      if (w == 1 && elect_one()) {
        uint32_t fb = bars + 8 * (B_FULL2 + 2 + wg);
        mbar_expect_tx(fb, 16384); tma_3d(sb + b2_slot(2 + wg), &mwo, 0, (2 + wg) * 64, 2 * cb, fb);
      }
      __syncwarp();
      TM(13);
    }
    bar_sync(NB_CONS, 256);
    if (wg == 1) {
      if (w == 0) {
        if (lane < 16) wait_flag(P.oflag + r128 * 32 + lane, epoch + 1);
        __syncwarp();
        TM(14);
#pragma unroll 1
        for (int kb = 0; kb < 16; kb++) {
          if (kb == 3) mbar_wait(bars + 8 * B_CV4, 0);
          if (kb >= 4) mbar_wait(bars + 8 * (B_EMPTY2 + (kb & 3)), ((kb >> 2) - 1) & 1);
          if (elect_one()) {
            uint32_t fb = bars + 8 * (B_FULL2 + (kb & 3));
            mbar_expect_tx(fb, 16384); tma_2d(sb + a2_slot(kb & 3), &moa, kb * 64, r128 * 128, fb);
            if (kb >= 4) { mbar_expect_tx(fb, 16384); tma_3d(sb + b2_slot(kb & 3), &mwo, 0, kb * 64, 2 * cb, fb); }
          }
          __syncwarp();
        }
      }
    } else {
      float acc[2][64];
      {
#pragma unroll 1
        for (int kb = 0; kb < 16; kb++) {
          const uint64_t da = mkdesc(sb + a2_slot(kb & 3), 16, 1024, 1), db = mkdesc(sb + b2_slot(kb & 3), 8192, 1024, 1);
          mbar_wait(bars + 8 * (B_FULL2 + (kb & 3)), (kb >> 2) & 1);

          wg_fence();
#pragma unroll
          for (int k = 0; k < 4; k++) {
            wg_p2_n128(acc[0], da + 2 * k, db + 128 * k, (kb | k) != 0);
            wg_p2_n128(acc[1], da + 512 + 2 * k, db + 128 * k, (kb | k) != 0);
          }
          wg_commit();
          if (kb > 0) { wg_wait<1>(); if (tid == 0) mbar_arrive(bars + 8 * (B_EMPTY2 + ((kb - 1) & 3))); }
        }
      }
      int ty;
      asm volatile("mov.u32 %0, %%tid.x;" : "=r"(ty));
      const int ln = ty & 31;
      TM(15);
      mbar_wait(bars + 8 * B_AT, 0);
      const int chl = (ln & 7) + ((ln >> 4) << 3), tc = 2 * w + ((ln >> 3) & 1), row = w * 16 + (ln & 15);
      const uint32_t at = sb + OFF_AT + chl * 128 + ((tc ^ (chl & 7)) << 4), gt = sb + OFF_GT + (w * 16 + (ln >> 2)) * 8;
      uint32_t a[2][4];
      ldsm4t(at, a[0][0], a[0][1], a[0][2], a[0][3]);
      wg_wait<0>();
      TM(16);
#pragma unroll
      for (int mb = 0; mb < 2; mb++) {
        const uint2 u0 = lds64(gt + mb * 512), u1 = lds64(gt + mb * 512 + 64);
        const float g0 = __uint_as_float(u0.x), h0 = __uint_as_float(u0.y), g1 = __uint_as_float(u1.x), h1 = __uint_as_float(u1.y);
        const uint32_t outs = sb + OFF_OUT + mb * 16384;
#pragma unroll
        for (int j = 0; j < 8; j++) {
          const int n = mb * 8 + j + 1;
          if (n < 16) ldsm4t(at + (n >> 3) * 16384 + (n & 7) * 2048, a[n & 1][0], a[n & 1][1], a[n & 1][2], a[n & 1][3]);
          const uint32_t* x = a[j & 1];
          const float* b = &acc[mb][8 * j];
          uint32_t o0 = pk(fmaf(g0, bflo(x[0]), h0 * b[0]), fmaf(g0, bfhi(x[0]), h0 * b[1]));
          uint32_t o1 = pk(fmaf(g1, bflo(x[1]), h1 * b[2]), fmaf(g1, bfhi(x[1]), h1 * b[3]));
          uint32_t o2 = pk(fmaf(g0, bflo(x[2]), h0 * b[4]), fmaf(g0, bfhi(x[2]), h0 * b[5]));
          uint32_t o3 = pk(fmaf(g1, bflo(x[3]), h1 * b[6]), fmaf(g1, bfhi(x[3]), h1 * b[7]));
          int cc = (2 * j + (ln >> 4)) & 7;
          stsm4(outs + (j >> 2) * 8192 + row * 128 + ((cc ^ (row & 7)) << 4), o0, o1, o2, o3);
        }
        fence_async_smem();
        bar_sync(NB_WG0, 128);
        if (ty == 0) {
          tma_st_2d(&mout, cb * 128, r128 * 128 + mb * 64, outs);
          tma_st_2d(&mout, cb * 128 + 64, r128 * 128 + mb * 64, outs + 8192);
          bulk_commit();
        }
      }
      TM(17);
      if (ty == 0) bulk_wait0_read();
      TM(18);
    }
  }
}

typedef CUresult (*EncFn)(CUtensorMap*, CUtensorMapDataType, cuuint32_t, void*, const cuuint64_t*, const cuuint64_t*, const cuuint32_t*, const cuuint32_t*,
                          CUtensorMapInterleave, CUtensorMapSwizzle, CUtensorMapL2promotion, CUtensorMapFloatOOBfill);
static void enc(EncFn fn, CUtensorMap* m, const void* p, int rank, cuuint64_t d0, cuuint64_t d1, cuuint64_t d2, cuuint64_t s1, cuuint64_t s2,
                cuuint32_t b0, cuuint32_t b1, cuuint32_t b2, CUtensorMapSwizzle sw) {
  cuuint64_t dims[3] = {d0, d1, d2}, str[2] = {s1, s2};
  cuuint32_t box[3] = {b0, b1, b2}, es[3] = {1, 1, 1};
  fn(m, CU_TENSOR_MAP_DATA_TYPE_BFLOAT16, rank, const_cast<void*>(p), dims, str, box, es, CU_TENSOR_MAP_INTERLEAVE_NONE, sw,
     CU_TENSOR_MAP_L2_PROMOTION_L2_128B, CU_TENSOR_MAP_FLOAT_OOB_FILL_NONE);
}

extern "C" void kernel_launch(void* const* d_in, const int* in_sizes, int n_in, void* d_out, int out_size) {
  (void)in_sizes; (void)n_in; (void)out_size;
  static EncFn fn = nullptr;
  static void *p_o = nullptr, *p_at = nullptr, *p_s[9];
  if (!fn) {
    void* f = nullptr; cudaDriverEntryPointQueryResult st;
    cudaGetDriverEntryPoint("cuTensorMapEncodeTiled", &f, cudaEnableDefault, &st);
    fn = (EncFn)f;
    cudaGetSymbolAddress(&p_o, g_o);
    cudaGetSymbolAddress(&p_at, g_aT);
    cudaGetSymbolAddress(&p_s[0], g_kv); cudaGetSymbolAddress(&p_s[1], g_gate); cudaGetSymbolAddress(&p_s[2], g_win); cudaGetSymbolAddress(&p_s[3], g_lut);
    cudaGetSymbolAddress(&p_s[4], g_epoch); cudaGetSymbolAddress(&p_s[5], g_kvflag); cudaGetSymbolAddress(&p_s[6], g_oflag);
    cudaGetSymbolAddress(&p_s[7], g_aflag); cudaGetSymbolAddress(&p_s[8], g_gflag);
    cudaFuncSetAttribute(fused_kernel, cudaFuncAttributeMaxDynamicSharedMemorySize, SMEM_TOTAL);
  }
  CUtensorMap mx, mw, mphi, mu, moa, mwo, mat, mout;
  enc(fn, &mx, d_in[0], 2, 1024, 2048, 1, 2048, 0, 32, 256, 1, CU_TENSOR_MAP_SWIZZLE_64B);
  enc(fn, &mw, d_in[10], 3, 1024, 1024, 3, 6144, 2048, 64, 32, 3, CU_TENSOR_MAP_SWIZZLE_128B);
  enc(fn, &mphi, d_in[11], 2, 32, 1024, 1, 64, 0, 32, 64, 1, CU_TENSOR_MAP_SWIZZLE_64B);
  enc(fn, &mu, d_in[0], 2, 1024, 2048, 1, 2048, 0, 8, 256, 1, CU_TENSOR_MAP_SWIZZLE_NONE);
  enc(fn, &moa, p_o, 2, 1024, 2048, 1, 2048, 0, 64, 128, 1, CU_TENSOR_MAP_SWIZZLE_128B);
  enc(fn, &mwo, d_in[12], 3, 64, 1024, 16, 2048, 128, 64, 64, 2, CU_TENSOR_MAP_SWIZZLE_128B);
  enc(fn, &mat, p_at, 2, 2048, 1024, 1, 4096, 0, 64, 128, 1, CU_TENSOR_MAP_SWIZZLE_128B);
  enc(fn, &mout, d_out, 2, 1024, 2048, 1, 2048, 0, 64, 64, 1, CU_TENSOR_MAP_SWIZZLE_128B);
  Params P;
  P.sbase = (const uint8_t*)d_in[1];
  for (int i = 0; i < 8; i++) P.soff[i] = (int)(((const uint8_t*)d_in[1 + i] - P.sbase) / 256);
  P.x = (const bf16*)d_in[0]; P.gw = (const bf16*)d_in[13];
  P.aT = (bf16*)p_at; P.kv = (float*)p_s[0]; P.gate = (float2*)p_s[1]; P.win = (uint8_t*)p_s[2]; P.lut = (const uint32_t*)p_s[3];
  P.epoch = (uint32_t*)p_s[4]; P.kvflag = (uint32_t*)p_s[5]; P.oflag = (uint32_t*)p_s[6]; P.aflag = (uint32_t*)p_s[7]; P.gflag = (uint32_t*)p_s[8];
  fused_kernel<<<128, 384, SMEM_TOTAL>>>(P, mx, mw, mphi, mu, moa, mwo, mat, mout);
}
```
